```python
import torch

def _softmax(x, axis=-1):
    return torch.softmax(x, dim=axis)

def _gelu(x):
    return torch.nn.functional.gelu(x, approximate='tanh')

def _silu(x):
    return torch.nn.functional.silu(x)

def _sigmoid(x):
    return torch.sigmoid(x)

def _layernorm(x, axis=-1, eps=1e-05):
    m = x.mean(dim=axis, keepdim=True)
    v = x.var(dim=axis, keepdim=True, unbiased=False)
    return (x - m) / torch.sqrt(v + eps)

def _scatter_add(tgt, idx, src, axis=0):
    return tgt.clone().index_add_(axis, idx, src)

def _segment_sum(src, seg, n):
    out = torch.zeros((n,) + src.shape[1:], dtype=src.dtype)
    return out.index_add_(0, seg, src)

def _pad(x, pw):
    flat = tuple((v for pair in reversed(pw) for v in pair))
    return torch.nn.functional.pad(x, flat)
kernel_name = 'concat_heads__ssm_conv_s4d__memory_aug_recurrent_mem_tr__prompt'

def setup_inputs():

    _w = lambda a: (lambda t: t.to(torch.bfloat16) if t.is_floating_point() else t)(torch.as_tensor(a))

    def _A_setup():
        Bsz, L, D, N = (1, 2048, 448, 256)
        return {'u': _w((lambda *s: torch.randn(*s, dtype=torch.bfloat16) * 0.05)(Bsz, L, D)), 'log_A_real': _w((lambda *s: torch.randn(*s, dtype=torch.bfloat16) * 6.4)(D, N) * 0.5), 'A_imag': _w((lambda *s: torch.randn(*s, dtype=torch.bfloat16) * 0.05)(D, N) * 3.14), 'C_real': _w((lambda *s: torch.randn(*s, dtype=torch.bfloat16) * 0.2)(D, N) / N ** 0.5), 'C_imag': _w((lambda *s: torch.randn(*s, dtype=torch.bfloat16) * 0.2)(D, N) / N ** 0.5), 'log_dt': _w((lambda *s: torch.randn(*s, dtype=torch.bfloat16) * 0.05)(D) * 0.5 - 4.0), 'D_skip': _w((lambda *s: torch.randn(*s, dtype=torch.bfloat16) * 0.05)(D))}
    _A_in = _A_setup()

    def _B_setup():
        B, S, Dm = (1, 2048, 448)
        H, Dh = (16, 256)
        M, seg = (8, 32)
        seg = min(seg, S)
        S = S // seg * seg
        return {'x': _w((lambda *s: torch.randn(*s, dtype=torch.bfloat16) * 0.05)(B, S, Dm)), 'mem0': _w((lambda *s: torch.randn(*s, dtype=torch.bfloat16) * 0.4)(B, M, Dm)), 'Wq': _w((lambda *s: torch.randn(*s, dtype=torch.bfloat16) * 6.4)(Dm, H, Dh) * Dm ** (-0.5)), 'Wk': _w((lambda *s: torch.randn(*s, dtype=torch.bfloat16) * 6.4)(Dm, H, Dh) * Dm ** (-0.5)), 'Wv': _w((lambda *s: torch.randn(*s, dtype=torch.bfloat16) * 0.4)(Dm, H, Dh) * Dm ** (-0.5)), 'Wo': _w((lambda *s: torch.randn(*s, dtype=torch.bfloat16) * 0.4)(H, Dh, Dm) * (H * Dh) ** (-0.5)), 'seg_len': seg}
    _B_in = _B_setup()
    return {'A_u': _A_in['u'], 'A_log_A_real': _A_in['log_A_real'], 'A_A_imag': _A_in['A_imag'], 'A_C_real': _A_in['C_real'], 'A_C_imag': _A_in['C_imag'], 'A_log_dt': _A_in['log_dt'], 'A_D_skip': _A_in['D_skip'], 'B_x': _B_in['x'], 'B_mem0': _B_in['mem0'], 'B_Wq': _B_in['Wq'], 'B_Wk': _B_in['Wk'], 'B_Wv': _B_in['Wv'], 'B_Wo': _B_in['Wo'], 'B_seg_len': _B_in['seg_len']}

def reference(A_u, A_log_A_real, A_A_imag, A_C_real, A_C_imag, A_log_dt, A_D_skip, B_x, B_mem0, B_Wq, B_Wk, B_Wv, B_Wo, B_seg_len):

    def _A_ref(u, log_A_real, A_imag, C_real, C_imag, log_dt, D_skip):
        L = u.shape[1]
        dt = torch.exp(log_dt)
        A = -torch.exp(log_A_real) + 1j * A_imag
        C = (C_real + 1j * C_imag) * dt[:, None]
        pos = (lambda x, dt: x.to(dt))(torch.arange(L), log_dt.dtype)
        P = torch.exp((A * dt[:, None])[:, :, None] * pos[None, None, :])
        K = 2.0 * torch.einsum('dn,dnl->dl', C, P).real
        L2 = 2 * L
        u_t = (lambda x, *d: x.permute(*d))(u, 0, 2, 1)
        Kf = (lambda x, *a, **k: torch.fft.rfft(x.float(), *a, **k))(K, L2)
        Uf = (lambda x, *a, **k: torch.fft.rfft(x.float(), *a, **k))(u_t, L2)
        y = (lambda x, *a, **k: torch.fft.irfft(x, *a, **k).to(torch.bfloat16))(Uf * Kf[None, :, :], L2)[:, :, :L]
        y = (lambda x, *d: x.permute(*d))(y, 0, 2, 1)
        return y + u * D_skip[None, None, :]

    def _B_ref(x, mem0, Wq, Wk, Wv, Wo, seg_len):
        B, S, Dm = x.shape
        H, Dh = (Wq.shape[1], Wq.shape[2])
        M = mem0.shape[1]
        scale = Dh ** (-0.5)
        n_seg = S // seg_len
        L = M + seg_len
        idx = torch.arange(L)
        mask = (idx[:, None] < M) | (idx[:, None] >= idx[None, :])
        mem = mem0
        outs = []
        for s in range(n_seg):
            xs = x[:, s * seg_len:(s + 1) * seg_len, :].clone()
            h = torch.concatenate([mem, xs], axis=1)
            q = torch.einsum('btd,dhe->bhte', h, Wq)
            k = torch.einsum('btd,dhe->bhte', h, Wk)
            v = torch.einsum('btd,dhe->bhte', h, Wv)
            scores = torch.einsum('bhqe,bhke->bhqk', q, k) * scale
            scores = torch.where(mask[None, None], scores, -1000000000.0)
            p = _softmax(scores, axis=-1)
            o = torch.einsum('bhqk,bhke->bhqe', p, v)
            o = torch.einsum('bhte,hed->btd', o, Wo)
            mem = o[:, :M, :].clone()
            outs.append(o[:, M:, :])
        return torch.concatenate(outs, axis=1)
    a = _A_ref(A_u, A_log_A_real, A_A_imag, A_C_real, A_C_imag, A_log_dt, A_D_skip)
    b = _B_ref(B_x, B_mem0, B_Wq, B_Wk, B_Wv, B_Wo, B_seg_len)
    return torch.concatenate([a, b], axis=-1)
```

```cpp
#include <cuda.h>
#include <cuda_runtime.h>
#include <cuda_bf16.h>
#include <cuda_fp16.h>
#include <stdint.h>
#include <string.h>

namespace {

constexpr int D = 448, S = 2048, NSEG = 64, DH = 256, NST = 256, OUTW = 896;
constexpr int RS = 16;

__device__ uint4 g_F[2 * 16 * 4 * 28 * 7 * 32];
__device__ __align__(128) uint8_t g_K[RS * 16 * 4 * 4 * 1792];
__device__ __align__(128) uint8_t g_V[RS * 16 * 56 * 512];
__device__ __align__(128) uint32_t g_P[RS * 16 * 14 * 32];
__device__ __align__(128) uint32_t g_U[RS * 16 * 56 * 32];
__device__ __align__(128) uint8_t g_ACC[98304];
__device__ unsigned g_FT[64 * 32];
__device__ unsigned g_CNT[NSEG * 32];
__device__ unsigned g_WD[32 * 32];
__device__ unsigned g_INIT, g_EXIT;
#define GT(k, i)

__host__ __device__ constexpr int sig0(int k) { return k == 6 ? 12 : 4 * (k >> 1) + (k & 1); }
__host__ __device__ constexpr int sig1(int k) { return k == 6 ? 13 : 4 * (k >> 1) + (k & 1) + 2; }
constexpr int SPIN = 1 << 22;

__device__ __forceinline__ uint32_t smem_u32(const void* p) { return (uint32_t)__cvta_generic_to_shared(p); }
__device__ __forceinline__ void mma16816(float* c, uint32_t a0, uint32_t a1, uint32_t a2, uint32_t a3, uint32_t b0, uint32_t b1) {
    asm volatile("mma.sync.aligned.m16n8k16.row.col.f32.bf16.bf16.f32 {%0,%1,%2,%3},{%4,%5,%6,%7},{%8,%9},{%0,%1,%2,%3};"
                 : "+f"(c[0]), "+f"(c[1]), "+f"(c[2]), "+f"(c[3]) : "r"(a0), "r"(a1), "r"(a2), "r"(a3), "r"(b0), "r"(b1));
}
__device__ __forceinline__ void mma16816z(float* c, uint32_t a0, uint32_t a1, uint32_t a2, uint32_t a3, uint32_t b0, uint32_t b1) {
    asm volatile("mma.sync.aligned.m16n8k16.row.col.f32.bf16.bf16.f32 {%0,%1,%2,%3},{%4,%5,%6,%7},{%8,%9},{%10,%10,%10,%10};"
                 : "=f"(c[0]), "=f"(c[1]), "=f"(c[2]), "=f"(c[3]) : "r"(a0), "r"(a1), "r"(a2), "r"(a3), "r"(b0), "r"(b1), "f"(0.f));
}
__device__ __forceinline__ void mma1688(float* c, uint32_t a0, uint32_t a1, uint32_t b0) {
    asm volatile("mma.sync.aligned.m16n8k8.row.col.f32.bf16.bf16.f32 {%0,%1,%2,%3},{%4,%5},{%6},{%0,%1,%2,%3};"
                 : "+f"(c[0]), "+f"(c[1]), "+f"(c[2]), "+f"(c[3]) : "r"(a0), "r"(a1), "r"(b0));
}
__device__ __forceinline__ void mmaq(float* c, const uint4& a, uint32_t b0, uint32_t b1) { mma16816(c, a.x, a.y, a.z, a.w, b0, b1); }
__device__ __forceinline__ void mmaqz(float* c, const uint4& a, uint32_t b0, uint32_t b1) { mma16816z(c, a.x, a.y, a.z, a.w, b0, b1); }
__device__ __forceinline__ uint32_t pack_bf16(float lo, float hi) {
    uint32_t r; asm("cvt.rn.bf16x2.f32 %0,%1,%2;" : "=r"(r) : "f"(hi), "f"(lo)); return r;
}
__device__ __forceinline__ uint32_t pack_bf16_again(float lo, float hi) {
    uint32_t r; asm("cvt.rn.relu.bf16x2.f32 %0,%1,%2;" : "=r"(r) : "f"(hi), "f"(lo)); return r;
}
__device__ __forceinline__ uint32_t pack_f16(float lo, float hi) {
    uint32_t r; asm("cvt.rn.f16x2.f32 %0,%1,%2;" : "=r"(r) : "f"(hi), "f"(lo)); return r;
}
__device__ __forceinline__ uint32_t prmt(uint32_t a, uint32_t b, uint32_t sel) { uint32_t r; asm("prmt.b32 %0,%1,%2,%3;" : "=r"(r) : "r"(a), "r"(b), "r"(sel)); return r; }
__device__ __forceinline__ uint32_t movm(uint32_t a) {
    uint32_t d; asm volatile("movmatrix.sync.aligned.m8n8.trans.b16 %0,%1;" : "=r"(d) : "r"(a)); return d;
}
__device__ __forceinline__ void ldsm4(uint32_t* r, uint32_t a) {
    asm volatile("ldmatrix.sync.aligned.m8n8.x4.shared.b16 {%0,%1,%2,%3},[%4];" : "=r"(r[0]), "=r"(r[1]), "=r"(r[2]), "=r"(r[3]) : "r"(a) : "memory");
}
__device__ __forceinline__ uint4 ldsm4q(uint32_t a) { uint32_t r[4]; ldsm4(r, a); return make_uint4(r[0], r[1], r[2], r[3]); }
__device__ __forceinline__ void stsm4(uint32_t a, const uint4& v) {
    asm volatile("stmatrix.sync.aligned.m8n8.x4.shared.b16 [%0],{%1,%2,%3,%4};" ::"r"(a), "r"(v.x), "r"(v.y), "r"(v.z), "r"(v.w) : "memory");
}
__device__ __forceinline__ void stsm2(uint32_t a, uint32_t x, uint32_t y) {
    asm volatile("stmatrix.sync.aligned.m8n8.x2.shared.b16 [%0],{%1,%2};" ::"r"(a), "r"(x), "r"(y) : "memory");
}
__device__ __forceinline__ uint4 lds128(uint32_t a) {
    uint4 v; asm volatile("ld.shared.v4.u32 {%0,%1,%2,%3},[%4];" : "=r"(v.x), "=r"(v.y), "=r"(v.z), "=r"(v.w) : "r"(a) : "memory"); return v;
}
__device__ __forceinline__ float4 lds128f(uint32_t a) {
    float4 v; asm volatile("ld.shared.v4.f32 {%0,%1,%2,%3},[%4];" : "=f"(v.x), "=f"(v.y), "=f"(v.z), "=f"(v.w) : "r"(a) : "memory"); return v;
}
__device__ __forceinline__ uint2 lds64(uint32_t a) {
    uint2 v; asm volatile("ld.shared.v2.u32 {%0,%1},[%2];" : "=r"(v.x), "=r"(v.y) : "r"(a) : "memory"); return v;
}
__device__ __forceinline__ float2 lds64f(uint32_t a) {
    float2 v; asm volatile("ld.shared.v2.f32 {%0,%1},[%2];" : "=f"(v.x), "=f"(v.y) : "r"(a) : "memory"); return v;
}
__device__ __forceinline__ uint32_t lds32(uint32_t a) {
    uint32_t v; asm volatile("ld.shared.u32 %0,[%1];" : "=r"(v) : "r"(a) : "memory"); return v;
}
__device__ __forceinline__ float lds32f(uint32_t a) { return __uint_as_float(lds32(a)); }
__device__ __forceinline__ void sts128(uint32_t a, uint32_t x, uint32_t y, uint32_t z, uint32_t w) {
    asm volatile("st.shared.v4.u32 [%0],{%1,%2,%3,%4};" ::"r"(a), "r"(x), "r"(y), "r"(z), "r"(w) : "memory");
}
__device__ __forceinline__ void sts64(uint32_t a, uint32_t x, uint32_t y) {
    asm volatile("st.shared.v2.u32 [%0],{%1,%2};" ::"r"(a), "r"(x), "r"(y) : "memory");
}
__device__ __forceinline__ void sts64f(uint32_t a, float x, float y) { sts64(a, __float_as_uint(x), __float_as_uint(y)); }
__device__ __forceinline__ void sts32(uint32_t a, uint32_t x) { asm volatile("st.shared.u32 [%0],%1;" ::"r"(a), "r"(x) : "memory"); }
__device__ __forceinline__ void sts32f(uint32_t a, float x) { sts32(a, __float_as_uint(x)); }
#define ADDR3(ins) "{.reg .u32 t; add.u32 t," ins "}"
template <int I> __device__ __forceinline__ uint4 lds128u(uint32_t a, uint32_t u) {
    uint4 v; asm volatile(ADDR3("%4,%5; ld.shared.v4.u32 {%0,%1,%2,%3},[t+%6];") : "=r"(v.x), "=r"(v.y), "=r"(v.z), "=r"(v.w) : "r"(a), "r"(u), "n"(I) : "memory"); return v;
}
template <int I> __device__ __forceinline__ float4 lds128fu(uint32_t a, uint32_t u) {
    const uint4 v = lds128u<I>(a, u); return make_float4(__uint_as_float(v.x), __uint_as_float(v.y), __uint_as_float(v.z), __uint_as_float(v.w));
}
template <int I> __device__ __forceinline__ uint2 lds64u(uint32_t a, uint32_t u) {
    uint2 v; asm volatile(ADDR3("%2,%3; ld.shared.v2.u32 {%0,%1},[t+%4];") : "=r"(v.x), "=r"(v.y) : "r"(a), "r"(u), "n"(I) : "memory"); return v;
}
template <int I> __device__ __forceinline__ float2 lds64fu(uint32_t a, uint32_t u) { const uint2 v = lds64u<I>(a, u); return make_float2(__uint_as_float(v.x), __uint_as_float(v.y)); }
template <int I> __device__ __forceinline__ uint4 ldsm4u(uint32_t a, uint32_t u) {
    uint4 v; asm volatile(ADDR3("%4,%5; ldmatrix.sync.aligned.m8n8.x4.shared.b16 {%0,%1,%2,%3},[t+%6];") : "=r"(v.x), "=r"(v.y), "=r"(v.z), "=r"(v.w) : "r"(a), "r"(u), "n"(I) : "memory"); return v;
}
template <int I> __device__ __forceinline__ uint4 ldsm4tu(uint32_t a, uint32_t u) {
    uint4 v; asm volatile(ADDR3("%4,%5; ldmatrix.sync.aligned.m8n8.x4.trans.shared.b16 {%0,%1,%2,%3},[t+%6];") : "=r"(v.x), "=r"(v.y), "=r"(v.z), "=r"(v.w) : "r"(a), "r"(u), "n"(I) : "memory"); return v;
}
__device__ __forceinline__ uint32_t uni(uint32_t v) { return __shfl_sync(0xffffffffu, v, 0); }
template <int I> __device__ __forceinline__ void sts128u(uint32_t a, uint32_t u, uint32_t x, uint32_t y, uint32_t z, uint32_t w) {
    asm volatile(ADDR3("%0,%1; st.shared.v4.u32 [t+%2],{%3,%4,%5,%6};") ::"r"(a), "r"(u), "n"(I), "r"(x), "r"(y), "r"(z), "r"(w) : "memory");
}
template <int I> __device__ __forceinline__ void sts64u(uint32_t a, uint32_t u, uint32_t x, uint32_t y) {
    asm volatile(ADDR3("%0,%1; st.shared.v2.u32 [t+%2],{%3,%4};") ::"r"(a), "r"(u), "n"(I), "r"(x), "r"(y) : "memory");
}
__device__ __forceinline__ uint32_t add_here(uint32_t a, uint32_t b) { uint32_t r; asm volatile("add.u32 %0,%1,%2;" : "=r"(r) : "r"(a), "r"(b)); return r; }
__device__ __forceinline__ uint8_t* add_here(uint8_t* p, uint32_t o) { uint8_t* r; asm volatile("{.reg .u64 t; cvt.u64.u32 t,%2; add.u64 %0,%1,t;}" : "=l"(r) : "l"(p), "r"(o)); return r; }
__device__ __forceinline__ uint32_t mapa(uint32_t a, uint32_t r) {
    uint32_t o; asm("mapa.shared::cluster.u32 %0,%1,%2;" : "=r"(o) : "r"(a), "r"(r)); return o;
}
__device__ __forceinline__ void st_async4(uint32_t dst, uint32_t bar, float x, float y, float z, float w) {
    asm volatile("st.async.weak.shared::cluster.mbarrier::complete_tx::bytes.v4.f32 [%0],{%1,%2,%3,%4},[%5];"
                 ::"r"(dst), "f"(x), "f"(y), "f"(z), "f"(w), "r"(bar) : "memory");
}
__device__ __forceinline__ void st_async2(uint32_t dst, uint32_t bar, float x, float y) {
    asm volatile("st.async.weak.shared::cluster.mbarrier::complete_tx::bytes.v2.f32 [%0],{%1,%2},[%3];"
                 ::"r"(dst), "f"(x), "f"(y), "r"(bar) : "memory");
}
__device__ __forceinline__ void st_async1(uint32_t dst, uint32_t bar, uint32_t x) {
    asm volatile("st.async.weak.shared::cluster.mbarrier::complete_tx::bytes.u32 [%0],%1,[%2];" ::"r"(dst), "r"(x), "r"(bar) : "memory");
}
__device__ __forceinline__ float ldr32f(uint32_t a) {
    float v; asm volatile("ld.shared::cluster.f32 %0,[%1];" : "=f"(v) : "r"(a) : "memory"); return v;
}
__device__ __forceinline__ void mbar_init(uint32_t bar, int cnt) { asm volatile("mbarrier.init.shared::cta.b64 [%0],%1;" ::"r"(bar), "r"(cnt) : "memory"); }
__device__ __forceinline__ void mbar_expect(uint32_t bar, int bytes) {
    asm volatile("mbarrier.arrive.expect_tx.shared::cta.b64 _,[%0],%1;" ::"r"(bar), "r"(bytes) : "memory");
}
__device__ __forceinline__ void mbar_arrive(uint32_t a) { asm volatile("mbarrier.arrive.release.cta.shared::cta.b64 _,[%0];" ::"r"(a) : "memory"); }
__device__ __forceinline__ void mbar_wait(uint32_t bar, uint32_t parity) {
    uint32_t ok; int it = 0;
    while (true) {
        asm volatile("{.reg .pred p; mbarrier.try_wait.parity.shared::cta.b64 p,[%1],%2; selp.u32 %0,1,0,p;}" : "=r"(ok) : "r"(bar), "r"(parity) : "memory");
        if (ok) break;
        if (++it > SPIN) __trap();
    }
}
__device__ __forceinline__ void mbar_wait_cl(uint32_t bar) {
    uint32_t ok; int it = 0;
    while (true) {
        asm volatile("{.reg .pred p; mbarrier.try_wait.parity.relaxed.cluster.shared::cta.b64 p,[%1],0; selp.u32 %0,1,0,p;}" : "=r"(ok) : "r"(bar) : "memory");
        if (ok) break;
        if (++it > SPIN) __trap();
    }
    asm volatile("fence.acquire.sync_restrict::shared::cluster.cluster;" ::: "memory");
}
__device__ __forceinline__ void bulk_g2s(uint32_t dst, const void* src, int bytes, uint32_t bar) {
    asm volatile("cp.async.bulk.shared::cluster.global.mbarrier::complete_tx::bytes [%0],[%1],%2,[%3];"
                 ::"r"(dst), "l"(src), "r"(bytes), "r"(bar) : "memory");
}
__device__ __forceinline__ void tma2d(uint32_t dst, const CUtensorMap* map, int x, int y, uint32_t bar) {
    asm volatile("cp.async.bulk.tensor.2d.shared::cluster.global.mbarrier::complete_tx::bytes [%0],[%1,{%2,%3}],[%4];"
                 ::"r"(dst), "l"(map), "r"(x), "r"(y), "r"(bar) : "memory");
}
__device__ __forceinline__ void tma3d(uint32_t dst, const CUtensorMap* map, int x, int y, int z, uint32_t bar) {
    asm volatile("cp.async.bulk.tensor.3d.shared::cluster.global.mbarrier::complete_tx::bytes [%0],[%1,{%2,%3,%4}],[%5];"
                 ::"r"(dst), "l"(map), "r"(x), "r"(y), "r"(z), "r"(bar) : "memory");
}
__device__ __forceinline__ void prefetch_l2(const void* p, int bytes) {
    asm volatile("cp.async.bulk.prefetch.L2.global [%0],%1;" ::"l"(p), "r"(bytes) : "memory");
}
__device__ __forceinline__ int fresh_lane() { int l; asm volatile("mov.u32 %0,%%laneid;" : "=r"(l)); return __shfl_sync(0xffffffffu, l, l); }
__device__ __forceinline__ bool elect_one() {
    uint32_t r; asm volatile("{.reg .pred p; elect.sync _|p,0xffffffff; selp.u32 %0,1,0,p;}" : "=r"(r)); return r;
}
__device__ __forceinline__ void bar_sync(int id, int n) { asm volatile("bar.sync %0,%1;" ::"r"(id), "r"(n) : "memory"); }
__device__ __forceinline__ void bar_arrive(int id, int n) { asm volatile("bar.arrive %0,%1;" ::"r"(id), "r"(n) : "memory"); }
__device__ __forceinline__ uint4 ld_relaxed4(const void* p) {
    uint4 v; asm volatile("ld.relaxed.gpu.global.v4.u32 {%0,%1,%2,%3},[%4];" : "=r"(v.x), "=r"(v.y), "=r"(v.z), "=r"(v.w) : "l"(p) : "memory"); return v;
}
__device__ __forceinline__ unsigned ld_relaxed(const unsigned* p) {
    unsigned v; asm volatile("ld.relaxed.gpu.global.u32 %0,[%1];" : "=r"(v) : "l"(p) : "memory"); return v;
}
__device__ __forceinline__ void st_relaxed(unsigned* p, unsigned v) { asm volatile("st.relaxed.gpu.global.u32 [%0],%1;" ::"l"(p), "r"(v) : "memory"); }
__device__ __forceinline__ void stg32(void* p, uint32_t v) { asm volatile("st.global.u32 [%0],%1;" ::"l"(p), "r"(v) : "memory"); }
__device__ __forceinline__ void red_inc(unsigned* p) { asm volatile("red.relaxed.gpu.global.add.u32 [%0],1;" ::"l"(p) : "memory"); }
__device__ __forceinline__ void fence_gpu() { asm volatile("fence.acq_rel.gpu;" ::: "memory"); }
__device__ __forceinline__ void wait_count(const unsigned* p, unsigned goal, unsigned sleep_ns) {
    int it = 0;
    while ((int)(ld_relaxed(p) - goal) < 0) { if (sleep_ns) __nanosleep(sleep_ns); if (++it > SPIN) __trap(); }
}
__device__ __forceinline__ void wait_count_warp(const unsigned* p, unsigned goal, unsigned sleep_ns) {
    int it = 0;
    while (__any_sync(0xffffffffu, (int)(ld_relaxed(p) - goal) < 0)) { if (sleep_ns) __nanosleep(sleep_ns); if (++it > SPIN) __trap(); }
}
__device__ __forceinline__ void red_bf16x8(void* p, uint32_t x, uint32_t y, uint32_t z, uint32_t w) {
    asm volatile("red.relaxed.gpu.global.add.noftz.v4.bf16x2 [%0],{%1,%2,%3,%4};" ::"l"(p), "r"(x), "r"(y), "r"(z), "r"(w) : "memory");
}
__device__ __forceinline__ void mbar_arrive_if(bool on, uint32_t a) {
    asm volatile("{.reg .pred p; setp.ne.b32 p,%1,0; @p mbarrier.arrive.release.cta.shared::cta.b64 _,[%0];}" ::"r"(a), "r"((int)on) : "memory");
}
__device__ __forceinline__ uint32_t any_reg() { uint32_t r; asm volatile("" : "=r"(r)); return r; }
__device__ __forceinline__ float ex2(float x) { float y; asm("ex2.approx.ftz.f32 %0,%1;" : "=f"(y) : "f"(x)); return y; }
__device__ __forceinline__ float rcp(float x) { float y; asm("rcp.approx.ftz.f32 %0,%1;" : "=f"(y) : "f"(x)); return y; }
__device__ __forceinline__ uint32_t clk() {
    uint32_t c; asm volatile("{.reg .u64 t; .reg .u32 h; mov.u64 t,%%clock64; mov.b64 {%0,h},t;}" : "=r"(c)::"memory"); return c;
}
__device__ __forceinline__ uint32_t hadd_bf(uint32_t a, uint32_t b) { uint32_t r; asm("add.rn.bf16x2 %0,%1,%2;" : "=r"(r) : "r"(a), "r"(b)); return r; }
__device__ __forceinline__ uint32_t hmul_bf(uint32_t a, uint32_t b) { uint32_t r; asm("mul.rn.bf16x2 %0,%1,%2;" : "=r"(r) : "r"(a), "r"(b)); return r; }
__device__ __forceinline__ uint32_t hsum4(uint32_t a, uint32_t b, uint32_t c, uint32_t d) { return hadd_bf(hadd_bf(a, b), hadd_bf(c, d)); }
__device__ __forceinline__ float4 sum4(float4 a, float4 b, float4 c, float4 d) {
    return make_float4((a.x + b.x) + (c.x + d.x), (a.y + b.y) + (c.y + d.y), (a.z + b.z) + (c.z + d.z), (a.w + b.w) + (c.w + d.w));
}
__device__ __forceinline__ void cluster_sync() { asm volatile("barrier.cluster.arrive.release.aligned; barrier.cluster.wait.acquire.aligned;" ::: "memory"); }
#define SCHED_FENCE(z, k) do { if ((z) == (k)) __trap(); } while (0)

template <int TB>
__device__ __forceinline__ void wgmma224(float* d, uint64_t da, uint64_t db, int accumulate) {
    asm volatile("{.reg .pred p; setp.ne.b32 p,%114,0;\n"
                 "wgmma.mma_async.sync.aligned.m64n224k16.f32.bf16.bf16 {%0,%1,%2,%3,%4,%5,%6,%7,%8,%9,%10,%11,%12,%13,%14,%15,%16,%17,%18,%19,%20,%21,%22,%23,%24,%25,%26,%27,%28,%29,%30,%31,%32,%33,%34,%35,%36,%37,%38,%39,%40,%41,%42,%43,%44,%45,%46,%47,%48,%49,%50,%51,%52,%53,%54,%55,%56,%57,%58,%59,%60,%61,%62,%63,%64,%65,%66,%67,%68,%69,%70,%71,%72,%73,%74,%75,%76,%77,%78,%79,%80,%81,%82,%83,%84,%85,%86,%87,%88,%89,%90,%91,%92,%93,%94,%95,%96,%97,%98,%99,%100,%101,%102,%103,%104,%105,%106,%107,%108,%109,%110,%111},%112,%113,p,1,1,0,%115;}"
                 : "+f"(d[0]), "+f"(d[1]), "+f"(d[2]), "+f"(d[3]), "+f"(d[4]), "+f"(d[5]), "+f"(d[6]), "+f"(d[7]), "+f"(d[8]), "+f"(d[9]), "+f"(d[10]), "+f"(d[11]), "+f"(d[12]), "+f"(d[13]), "+f"(d[14]), "+f"(d[15]), "+f"(d[16]), "+f"(d[17]), "+f"(d[18]), "+f"(d[19]), "+f"(d[20]), "+f"(d[21]), "+f"(d[22]), "+f"(d[23]), "+f"(d[24]), "+f"(d[25]), "+f"(d[26]), "+f"(d[27]), "+f"(d[28]), "+f"(d[29]), "+f"(d[30]), "+f"(d[31]), "+f"(d[32]), "+f"(d[33]), "+f"(d[34]), "+f"(d[35]), "+f"(d[36]), "+f"(d[37]), "+f"(d[38]), "+f"(d[39]), "+f"(d[40]), "+f"(d[41]), "+f"(d[42]), "+f"(d[43]), "+f"(d[44]), "+f"(d[45]), "+f"(d[46]), "+f"(d[47]), "+f"(d[48]), "+f"(d[49]), "+f"(d[50]), "+f"(d[51]), "+f"(d[52]), "+f"(d[53]), "+f"(d[54]), "+f"(d[55]), "+f"(d[56]), "+f"(d[57]), "+f"(d[58]), "+f"(d[59]), "+f"(d[60]), "+f"(d[61]), "+f"(d[62]), "+f"(d[63]), "+f"(d[64]), "+f"(d[65]), "+f"(d[66]), "+f"(d[67]), "+f"(d[68]), "+f"(d[69]), "+f"(d[70]), "+f"(d[71]), "+f"(d[72]), "+f"(d[73]), "+f"(d[74]), "+f"(d[75]), "+f"(d[76]), "+f"(d[77]), "+f"(d[78]), "+f"(d[79]), "+f"(d[80]), "+f"(d[81]), "+f"(d[82]), "+f"(d[83]), "+f"(d[84]), "+f"(d[85]), "+f"(d[86]), "+f"(d[87]), "+f"(d[88]), "+f"(d[89]), "+f"(d[90]), "+f"(d[91]), "+f"(d[92]), "+f"(d[93]), "+f"(d[94]), "+f"(d[95]), "+f"(d[96]), "+f"(d[97]), "+f"(d[98]), "+f"(d[99]), "+f"(d[100]), "+f"(d[101]), "+f"(d[102]), "+f"(d[103]), "+f"(d[104]), "+f"(d[105]), "+f"(d[106]), "+f"(d[107]), "+f"(d[108]), "+f"(d[109]), "+f"(d[110]), "+f"(d[111])
                 : "l"(da), "l"(db), "r"(accumulate), "n"(TB));
}
__device__ __forceinline__ uint64_t sdesc(uint32_t addr, uint32_t lbo, uint32_t sbo, uint64_t swizzle) {
    return (uint64_t)((addr & 0x3FFFF) >> 4) | ((uint64_t)(lbo >> 4) << 16) | ((uint64_t)(sbo >> 4) << 32) | (swizzle << 62);
}
__device__ __forceinline__ void wg_fence() { asm volatile("wgmma.fence.sync.aligned;" ::: "memory"); }
__device__ __forceinline__ void wg_commit() { asm volatile("wgmma.commit_group.sync.aligned;" ::: "memory"); }
template <int N> __device__ __forceinline__ void wg_wait() { asm volatile("wgmma.wait_group.sync.aligned %0;" ::"n"(N) : "memory"); }
constexpr float LOG2E = 1.4426950408889634f;
constexpr uint32_t ONE2 = 0x3f803f80u;
constexpr uint32_t CNT16 = 0x41800000u;
constexpr uint32_t SAFE_LO = (127u - 40u) << 23, SAFE_SPAN = 80u << 23;

constexpr int C_R = 0;
constexpr int C_U = C_R + 8 * 2064 * 4;
constexpr int C_T = C_U + 8 * 24 * 272;
constexpr int C_TW = 53 * 144;
constexpr int C_Y = C_T;
constexpr int C_END = C_T + 8 * C_TW;

struct SsmArgs { const __nv_bfloat16 *u, *lar, *aim, *cre, *cim, *ldt, *dsk; __nv_bfloat16* out; };
struct cpx { float r, i; };
__device__ __forceinline__ cpx cmul(cpx a, cpx b) { return {fmaf(a.r, b.r, -a.i * b.i), fmaf(a.r, b.i, a.i * b.r)}; }
__device__ __forceinline__ cpx cexp(float er, float wi, float p) {
    const float e = ex2(er * p), x = wi * p;
    const float k = rintf(x * 0.15915494309189535f);
    const float r = fmaf(k, 1.7484555314695172e-07f, fmaf(k, -6.2831854820251465f, x));
    return {e * __cosf(r), e * __sinf(r)};
}

__device__ __forceinline__ void ssm_kernel_values(uint32_t tb, uint32_t rdst, int d, const SsmArgs& p) {
    const int lane = threadIdx.x & 31, g = lane >> 2, t = lane & 3;
    const uint4 v0 = __ldg((const uint4*)(p.lar + d * NST) + lane), v1 = __ldg((const uint4*)(p.aim + d * NST) + lane);
    const uint4 v2 = __ldg((const uint4*)(p.cre + d * NST) + lane), v3 = __ldg((const uint4*)(p.cim + d * NST) + lane);
    const float dt = __bfloat162float(__float2bfloat16(expf(__bfloat162float(p.ldt[d]))));
    const int o2 = g < 4 ? 256 + 2 * g : 512 + 256 * ((g - 4) >> 1) + 4 * (g & 1), o3 = 1024 + 256 * min(g, 4);
    float acc[2][4][4];
#pragma unroll
    for (int i = 0; i < 2; i++)
#pragma unroll
        for (int j = 0; j < 4; j++) acc[i][j][0] = acc[i][j][1] = acc[i][j][2] = acc[i][j][3] = 0.f;
    const uint32_t wa = tb + lane * 4, ra = tb + g * 144 + t * 4;
    uint32_t la[4] = {v0.x, v0.y, v0.z, v0.w}, ai[4] = {v1.x, v1.y, v1.z, v1.w}, cr[4] = {v2.x, v2.y, v2.z, v2.w}, ci[4] = {v3.x, v3.y, v3.z, v3.w};
#pragma unroll 1
    for (int it = 0; it < 8; it++) {
        const float er = (-__bfloat162float(__float2bfloat16(expf(__uint_as_float(la[0] << 16)))) * dt) * LOG2E;
        const float wi = __uint_as_float(ai[0] << 16) * dt;
        const cpx c = {2.f * (__uint_as_float(cr[0] << 16) * dt), 2.f * (__uint_as_float(ci[0] << 16) * dt)};
#pragma unroll
        for (int q = 0; q < 4; q++) {
            la[q] = __funnelshift_r(la[q], q < 3 ? la[q + 1] : 0u, 16); ai[q] = __funnelshift_r(ai[q], q < 3 ? ai[q + 1] : 0u, 16);
            cr[q] = __funnelshift_r(cr[q], q < 3 ? cr[q + 1] : 0u, 16); ci[q] = __funnelshift_r(ci[q], q < 3 ? ci[q + 1] : 0u, 16);
        }
        const cpx w1 = cexp(er, wi, 1.f), w8 = cexp(er, wi, 8.f), w64 = cexp(er, wi, 64.f), w256 = cexp(er, wi, 256.f);
        const cpx w2 = cmul(w1, w1), w4 = cmul(w2, w2);
        __syncwarp();
        auto putx = [&](int row, cpx x) { sts32(wa + row * 144, pack_bf16(x.r, -x.i)); };
        auto puty = [&](int row, cpx y) { sts32(wa + row * 144, pack_bf16(y.r, y.i)); };
        {
            cpx x = c; putx(0, x);
#pragma unroll
            for (int k = 1; k < 8; k++) { x = cmul(x, w1); putx(k, x); }
            cpx z = cmul(c, w256); x = z; putx(8, x);
#pragma unroll
            for (int k = 1; k < 4; k++) { x = cmul(x, w2); putx(8 + k, x); }
            z = cmul(z, w256); putx(12, z); putx(13, cmul(z, w4));
            z = cmul(z, w256); putx(14, z); putx(15, cmul(z, w4));
#pragma unroll
            for (int k = 0; k < 5; k++) { z = cmul(z, w256); putx(16 + k, z); }
            cpx y[4] = {{1.f, 0.f}, w64, cmul(w64, w64), {0.f, 0.f}};
            y[3] = cmul(y[2], w64);
#pragma unroll
            for (int k = 0; k < 8; k++)
#pragma unroll
                for (int j = 0; j < 4; j++) { puty(21 + 8 * j + k, y[j]); if (k < 7) y[j] = cmul(y[j], w8); }
        }
        __syncwarp();
#pragma unroll
        for (int kk = 0; kk < 4; kk++) {
            uint32_t xa[2][3], yb[2][4];
#pragma unroll
            for (int z = 0; z < 2; z++) {
                const uint32_t a = ra + kk * 32 + z * 16;
                xa[z][0] = lds32(a); xa[z][1] = lds32(a + 8 * 144);
                xa[z][2] = lds32(a + 16 * 144);
#pragma unroll
                for (int j = 0; j < 4; j++) yb[z][j] = lds32(a + (21 + 8 * j) * 144);
            }
#pragma unroll
            for (int j = 0; j < 4; j++) {
                mma16816(acc[0][j], xa[0][0], xa[0][1], xa[1][0], xa[1][1], yb[0][j], yb[1][j]);
                mma16816(acc[1][j], xa[0][2], xa[0][2], xa[1][2], xa[1][2], yb[0][j], yb[1][j]);
            }
        }
    }
    __syncwarp();
    auto put16 = [&](int pos, float v) { asm volatile("st.shared.u16 [%0],%1;" ::"r"(tb + pos * 2), "h"(__bfloat16_as_ushort(__float2bfloat16(v))) : "memory"); };
#pragma unroll
    for (int j = 0; j < 4; j++)
#pragma unroll
        for (int e = 0; e < 2; e++) {
            const int cb = 64 * j + 16 * t + 8 * e;
            put16(g + cb, acc[0][j][e]); put16(o2 + cb, acc[0][j][2 + e]);
            if (g < 5) put16(o3 + cb, acc[1][j][e]);
        }
    __syncwarp();
    uint32_t prev = 0;
#pragma unroll 4
    for (int i = 0; i < 64; i++) {
        const int y = lane + 32 * i;
        const int pos = (int)__bfloat162float(__float2bfloat16((float)y));
        uint32_t k; asm volatile("{.reg .u16 h; ld.shared.u16 h,[%1]; cvt.u32.u16 %0,h;}" : "=r"(k) : "r"(tb + pos * 2) : "memory");
        uint32_t km = __shfl_up_sync(0xffffffffu, k, 1);
        if (lane == 0) km = prev;
        prev = __shfl_sync(0xffffffffu, k, 31);
        sts32(rdst + y * 4, k | (km << 16));
    }
}

__device__ __forceinline__ void ssm_unit(uint32_t sb, uint8_t* smem, int d0, const SsmArgs& p, int barid) {
    const int tid = threadIdx.x, lane = tid & 31, ch = __shfl_sync(0xffffffffu, tid >> 5, 0);
    const int g = lane >> 2, t = lane & 3;
    if (lane < 16) sts32(sb + C_R + ch * 8256 + lane * 4, 0u);
    for (int i = lane; i < 136; i += 32) sts128(sb + C_U + ch * 6528 + i * 16, 0u, 0u, 0u, 0u);
    uint4 uv[8];
#pragma unroll
    for (int i = 0; i < 8; i++) uv[i] = __ldg((const uint4*)(p.u + (size_t)(2 * (tid + 256 * (i >> 1)) + (i & 1)) * D + d0));
    const float dk = __bfloat162float(p.dsk[d0 + ch]);
    ssm_kernel_values(sb + C_T + ch * C_TW, sb + C_R + ch * 8256 + 64, d0 + ch, p);
#pragma unroll
    for (int i = 0; i < 4; i++) {
        const int tt = 2 * (tid + 256 * i);
        const uint4 v0 = uv[2 * i], v1 = uv[2 * i + 1];
        const uint32_t a = sb + C_U + ((tt >> 7) + 8) * 272 + (tt & 127) * 2;
        sts32(a, __byte_perm(v0.x, v1.x, 0x5410)); sts32(a + 6528, __byte_perm(v0.x, v1.x, 0x7632));
        sts32(a + 2 * 6528, __byte_perm(v0.y, v1.y, 0x5410)); sts32(a + 3 * 6528, __byte_perm(v0.y, v1.y, 0x7632));
        sts32(a + 4 * 6528, __byte_perm(v0.z, v1.z, 0x5410)); sts32(a + 5 * 6528, __byte_perm(v0.z, v1.z, 0x7632));
        sts32(a + 6 * 6528, __byte_perm(v0.w, v1.w, 0x5410)); sts32(a + 7 * 6528, __byte_perm(v0.w, v1.w, 0x7632));
    }
    bar_sync(barid, 256);
    float acc[8][2][4];
#pragma unroll
    for (int i = 0; i < 8; i++)
#pragma unroll
        for (int j = 0; j < 2; j++) acc[i][j][0] = acc[i][j][1] = acc[i][j][2] = acc[i][j][3] = 0.f;
    const uint32_t ra = sb + C_R + ch * 8256 + 64 + (g - 2 * t) * 4;
    const uint32_t ua = sb + C_U + ch * 6528 + (8 + (lane & 7)) * 272 + (lane >> 3) * 16;
    auto step = [&](int m, bool first, bool both) {
        uint32_t q[15][4];
#pragma unroll
        for (int i = 0; i < 15; i++) {
            if (first && i < 7) continue;
            const uint32_t a = ra + (128 * m + 16 * (i - 7)) * 4;
            asm volatile("ld.shared.u32 %0,[%1];" : "=r"(q[i][0]) : "r"(a)); asm volatile("ld.shared.u32 %0,[%1];" : "=r"(q[i][1]) : "r"(a + 32));
            asm volatile("ld.shared.u32 %0,[%1];" : "=r"(q[i][2]) : "r"(a - 32)); q[i][3] = q[i][0];
        }
#pragma unroll
        for (int kp = 0; kp < 4; kp++) {
            uint32_t b0[4], b1[4];
            if (both) ldsm4(b0, ua - m * 272 + kp * 64);
            ldsm4(b1, ua + (8 - m) * 272 + kp * 64);
#pragma unroll
            for (int kk = 0; kk < 2; kk++) {
                const int kb = 2 * kp + kk;
#pragma unroll
                for (int mb = 0; mb < 8; mb++) {
                    if (first && mb < kb) continue;
                    const uint32_t* a = q[mb - kb + 7];
                    if (both) mma16816(acc[mb][0], a[0], a[1], a[2], a[3], b0[2 * kk], b0[2 * kk + 1]);
                    mma16816(acc[mb][1], a[0], a[1], a[2], a[3], b1[2 * kk], b1[2 * kk + 1]);
                }
            }
        }
    };
    step(0, true, true);
#pragma unroll 1
    for (int m = 1; m < 8; m++) step(m, false, true);
#pragma unroll 1
    for (int m = 8; m < 16; m++) step(m, false, false);
#pragma unroll
    for (int mb = 0; mb < 8; mb++)
#pragma unroll
        for (int j = 0; j < 2; j++)
#pragma unroll
            for (int e = 0; e < 4; e++) {
                const int a = 8 * j + 2 * t + (e & 1), b = 16 * mb + g + 8 * (e >> 1), tt = 128 * a + b;
                const float uu = __bfloat162float(*(const __nv_bfloat16*)(smem + C_U + ch * 6528 + (a + 8) * 272 + b * 2));
                const float y = __bfloat162float(__float2bfloat16(acc[mb][j][e])) + __bfloat162float(__float2bfloat16(uu * dk));
                *(__nv_bfloat16*)(smem + C_Y + tt * 16 + (((ch >> 1) ^ t) << 2) + (ch & 1) * 2) = __float2bfloat16(y);
            }
    bar_sync(barid, 256);
#pragma unroll
    for (int i = 0; i < 8; i++) {
        const int tt = tid + 256 * i, x = i & 3;
        const uint4 v = lds128(sb + C_Y + tt * 16);
        const uint32_t w4[4] = {v.x, v.y, v.z, v.w};
        *(uint4*)(p.out + (size_t)tt * OUTW + d0) = make_uint4(w4[0 ^ x], w4[1 ^ x], w4[2 ^ x], w4[3 ^ x]);
    }
    bar_sync(barid, 256);
}

#define TRIG_DELAY 0
#define XXN 4
#define UW0 7
#define PF 0
#define CLUSTER 4
#define TW0 1
#define GO_DEP 8
#define POLL_DELAY 400
constexpr int S_V = 0, S_KO = 7168, S_KS = 14336, S_X = 21504, S_ONE = 29184, STGB = 29696;
constexpr int R_STG = 0;
constexpr int R_WB = R_STG + 4 * STGB, WB = 8192;
constexpr int W_W0 = 0;
constexpr int W_MB = 3584, W_TB = 5632, W_SMI = 7680;
constexpr int W_UP = 3584, W_QRT = 5632;
constexpr int W_TAB = 4 * WB + 6144;
constexpr int R_SMM = R_WB + 8 * WB;
constexpr int R_LS = R_SMM + 4096;
constexpr int R_ALIAS_END = R_LS + 10240;
constexpr int R_MISC = (R_ALIAS_END > C_END ? R_ALIAS_END : C_END);
constexpr int R_BAR = R_MISC + 16;
constexpr int B_KV = 0, B_SM = 512, B_LS = 1024, B_H = 1536, B_PUB = 2048, B_Z = 2560;
constexpr int R_SMEM = R_BAR + 3072;
static_assert(R_SMEM <= 232448, "smem");
enum { BR_MB = 1, BR_SM = 2, BR_UP = 3, BR_RED = 4, BR_PRO = 5, BR_ALL = 6, BR_POLL = 8, BR_GO = 12 };

#define DBG(i)

__device__ __forceinline__ uint32_t acc_off(int c, int q, int lane) {
    return (lane & 7) * 16 + ((lane >> 3) & 1) * 256 + (lane >> 4) * 1024 + (q & 1) * 2048 + (q >> 1) * 16384 + c * 4096;
}
__device__ __forceinline__ int tile_of(int q, int i) { return i == 3 ? 3 + 8 * (q >> 1) : (q == 3 && i == 2 ? 7 : 4 * q + i); }
__device__ __forceinline__ uint32_t acc_slot(int s) { return (s & 1) * 128 + (s & 2) * 256 + (s & 4) * 8192; }

__global__ void __cluster_dims__(CLUSTER, 1, 1) __launch_bounds__(384, 1)
k_rec(const __grid_constant__ CUtensorMap mapXs, const SsmArgs ssm, const uint8_t* x, const __nv_bfloat16* __restrict__ mem0,
      const uint8_t* wq, const uint8_t* wk, const uint8_t* wv, const uint8_t* wo, unsigned ntotal, const uint32_t zero) {
    extern __shared__ __align__(1024) uint8_t smem[];
    const uint32_t sb = smem_u32(smem);
    const int tid = threadIdx.x, wid = __shfl_sync(0xffffffffu, tid >> 5, 0), w = wid & 3;
    const int h = blockIdx.x >> 2, c = blockIdx.x & 3;
    const int rk = blockIdx.x & (CLUSTER - 4);
    uint8_t* const accb = (uint8_t*)(((uintptr_t)g_ACC + 32767) & ~(uintptr_t)32767);

    asm volatile("griddepcontrol.launch_dependents;" ::: "memory");
    if (tid == 0) GT(0, 0);
    if (wid == 8 && PF && elect_one()) {
        if (PF == 1) {
#pragma unroll 1
            for (int i = 0; i < 7; i++) { prefetch_l2(wq + blockIdx.x * 57344 + i * 8192, 8192); prefetch_l2(wo + blockIdx.x * 57344 + i * 8192, 8192); }
#pragma unroll 1
            for (int i = 0; i < 7; i++) { prefetch_l2(wk + (i * 64 + blockIdx.x) * 8192, 8192); prefetch_l2(wv + (i * 64 + blockIdx.x) * 8192, 8192); }
        } else if (PF == 2) {
            prefetch_l2(wk + blockIdx.x * 8192, 8192); prefetch_l2(wv + blockIdx.x * 8192, 8192);
            prefetch_l2(wq + blockIdx.x * 57344, 57344); prefetch_l2(wo + blockIdx.x * 57344, 57344);
#pragma unroll 1
            for (int i = 1; i < 7; i++) { prefetch_l2(wk + (i * 64 + blockIdx.x) * 8192, 8192); prefetch_l2(wv + (i * 64 + blockIdx.x) * 8192, 8192); }
        } else {
#pragma unroll 1
            for (int i = 0; i < 7; i++) { prefetch_l2(wk + (i * 64 + blockIdx.x) * 8192, 8192); prefetch_l2(wv + (i * 64 + blockIdx.x) * 8192, 8192); }
        }
        prefetch_l2(x + blockIdx.x * 28672, 28672);
    }
    mbar_init(sb + R_BAR + tid * 8, 1);
    asm volatile("fence.mbarrier_init.release.cluster;" ::: "memory");
    if (tid < 192) mbar_expect(sb + R_BAR + tid * 8, tid < 64 ? S_ONE - (4 - XXN) * 1792 : (tid < 128 ? 1536 :
        (c < 2 ? 3072 : 5120)
        ));
    if (tid == 288) sts32(sb + R_MISC, ld_relaxed(&g_EXIT) / ntotal);
    __syncthreads();

    if (wid < 8) {
        asm volatile("setmaxnreg.inc.sync.aligned.u32 232;");
        if (wid == 0) {
            const int lane = tid & 31;
            const int q = h >> 2, l = (h & 3) * 8 + (lane & 7);
            const uint32_t* mp = (const uint32_t*)(mem0 + (l >> 2) * D + 112 * c) + (l & 3);
            uint4 v = make_uint4(0, 0, 0, 0);
            if (lane < 8) v = make_uint4(mp[4 * tile_of(q, 0)], mp[4 * tile_of(q, 1)], mp[4 * tile_of(q, 2)],
                                         ((mp[4 * tile_of(q, 3)] >> (16 * (q & 1))) & 0xffffu) | CNT16);
            *(uint4*)(accb + acc_off(c, q, l) + acc_slot(lane >> 3)) = v;
            *(uint4*)(accb + acc_off(c, q, l) + acc_slot(4 + (lane >> 3))) = make_uint4(0, 0, 0, 0);
            __syncwarp();
            if (lane == 0) { fence_gpu(); red_inc(&g_INIT); }
        }
        if (blockIdx.x < D / 8) ssm_unit(sb, smem, blockIdx.x * 8, ssm, BR_PRO);
        asm volatile("fence.proxy.async.shared::cta;" ::: "memory");
        if (tid == 0) GT(0, 1);
        bar_sync(BR_ALL, 288);
        auto load_weights = [&](uint4 (&wr)[7][6], int lane) {
            wait_count_warp(g_FT + ((wid >> 2) * 32 + 2 * h + (c >> 1)) * 32 + (lane & 1), lds32(sb + R_MISC) * 32 + min(w + 1, 4 - (lane & 1)), 40);
            fence_gpu();
            const uint4* fp = g_F + ((((wid >> 2) * 16 + h) * 4 + c) * 28 + 7 * w) * 224 + lane;
            uint4 w0[7];
#pragma unroll
            for (int m = 0; m < 7; m++) w0[m] = __ldcg(fp + m * 32);
#pragma unroll
            for (int k = 0; k < 6; k++)
#pragma unroll
                for (int m = 0; m < 7; m++) wr[m][k] = __ldcg(fp + (k + 1) * 224 + m * 32);
#pragma unroll
            for (int m = 0; m < 7; m++) sts128(sb + R_WB + wid * WB + lane * 16 + m * 512, w0[m].x, w0[m].y, w0[m].z, w0[m].w);
            if (wid < 4) sts128(sb + R_STG + w * STGB + S_ONE + lane * 16, ONE2, ONE2, ONE2, ONE2);
            if (wid == 4) sts128(sb + R_WB + 4 * WB + W_QRT, 0x3e803e80u, 0x3e803e80u, 0x3e803e80u, 0x3e803e80u);
            cluster_sync();
        };
        if (wid < 4) {
            asm volatile("setmaxnreg.inc.sync.aligned.u32 248;");
            const int lane = fresh_lane(), g = lane >> 2;
            const uint32_t l16 = sb + lane * 16, l8 = sb + lane * 8;
            uint4 wr[7][6];
            load_weights(wr, lane);
            const uint32_t r2 = uni(mapa(sb, 2) - mapa(sb, 0));
            const uint32_t uw = uni(R_WB + w * WB), uc = uni(R_WB + c * WB), u2 = uni((tile_of(w, 2) - 4 * w) * 128);
            const uint32_t upoll = uni(acc_off(w, 0, 0)), ured = uni(acc_off(c, w, 0)), uk = uni(S_KO + w * 1792), uv = uni(S_V + 4 * w * 512);
            const int src = 16 * (w & 1) + (lane >> 1);
            const uint32_t sia = sb + R_WB + W_SMI + (w >> 1) * 256 + src * 8;
            {
                const uint32_t ua = sb + R_WB + (4 + (lane >> 3)) * WB + W_UP + (lane & 7) * 16 + 4 * w * 128;
                sts128u<W_TAB>(l16, uw, mapa(sb + R_SMM + (w < 2 ? c * 256 + src * 8 : 1024 + c * 128 + src * 4), rk + (lane & 1)), mapa(sb + R_BAR + B_SM, rk + (lane & 1)), acc_off(0, 0, lane), 0u);
                sts128u<W_TAB + 512>(l16, uw, l8 + (((g ^ w) & 1) ? S_ONE : S_V + tile_of(w, 3) * 512), ua,
                                     ((lane ^ w) & 1) ? sb + R_WB + 4 * WB + W_QRT : ua + (tile_of(w, 3) - 4 * w) * 128,
                                     sb + R_SMM + 1024 + (lane & 7) * 16 + (lane >> 4) * 128 + ((lane >> 3) & 1) * 256);
            }
            const bool wodd = w & 1;
            uint32_t t0 = clk() - POLL_DELAY;
            uint4 ub = make_uint4(0, 0, 0, 0);
            const uint8_t* pp = accb + acc_off(w, 0, lane);
            auto put_u = [&](int sl) {
                const uint32_t l4 = add_here(l8, -sb) >> 1;
                uint8_t* p = add_here((uint8_t*)(g_U + (((sl & (RS - 1)) * 64 + blockIdx.x) * 14 + 4 * w) * 32), l4);
                stg32(p, ub.x); stg32(p + 128, ub.y); stg32(p + (int)u2, ub.z);
                if (!(((l4 >> 4) ^ w) & 1)) stg32(p + (wodd ? -128 : 384), ub.w);
            };
#pragma unroll 1
            for (int s = 0; s < NSEG; s++) {
                const uint32_t par = uni((s & 1) * 2048), bar = uni(sb + R_BAR + s * 8), stg = uni(R_STG + (s & 3) * STGB), ksa = uni(stg + uk);
                uint4 w0[7];
                auto load_w0 = [&]() {
                    w0[0] = lds128u<0>(l16, uw); w0[1] = lds128u<512>(l16, uw); w0[2] = lds128u<1024>(l16, uw); w0[3] = lds128u<1536>(l16, uw);
                    w0[4] = lds128u<2048>(l16, uw); w0[5] = lds128u<2560>(l16, uw); w0[6] = lds128u<3072>(l16, uw);
                };
                mbar_wait(bar + B_KV, 0);
                while ((int)(clk() - t0) < POLL_DELAY) {}
                DBG(0);
                uint32_t b[14]; int it = 0;
                auto take = [&](const uint4& v0, const uint4& v1, const uint4& v2, const uint4& v3) {
                    const uint32_t mn = min(min(v0.w, v1.w), v2.w), sel = 0x5410u ^ (mn & zero);
                    b[0] = v0.x; b[1] = v0.y; b[2] = v0.z ^ zero; b[3] = prmt(v0.w, v1.w, sel);
                    b[4] = v1.x; b[5] = v1.y; b[6] = v1.z ^ zero; b[7] = v3.z ^ (b[3] & zero);
                    b[8] = v2.x; b[9] = v2.y; b[10] = v2.z ^ zero; b[11] = prmt(v2.w, v3.w, sel);
                    b[12] = v3.x; b[13] = v3.y;
                    sts128u<W_MB>(l16, uw, b[0], b[1], b[2], b[3]); sts128u<W_MB + 512>(l16, uw, b[4], b[5], b[6], b[7]);
                    sts128u<W_MB + 1024>(l16, uw, b[8], b[9], b[10], b[11]); sts64u<W_MB + 1536>(l16, uw, b[12], b[13]);
                    return __all_sync(0xffffffffu, mn >= CNT16 && v3.w >= CNT16);
                };
                uint4 v0 = ld_relaxed4(pp), v1 = ld_relaxed4(pp + 2048), v2 = ld_relaxed4(pp + 16384), v3 = ld_relaxed4(pp + 18432);
                load_w0();
                const uint4 ta = lds128u<W_TAB>(l16, uw);
                uint4 k0 = lds128u<0>(l16, ksa);
                const uint4 k1 = lds128u<512>(l16, ksa), k2 = lds128u<1024>(l16, ksa);
                const uint2 k3 = lds64u<1536>(l8, ksa);
                bar_arrive(BR_POLL + w, 64);
                if (s > 0) put_u(s - 1);
                {
                    sts128u<W_TAB + 1024>(l16, uw, ta.x + par, ta.y + s * 8, ta.x + par + r2, ta.y + s * 8 + r2);
                    const uint64_t rp = (uint64_t)(accb + (acc_slot(s + 1) + ured + ta.z)), pn = (uint64_t)(accb + (acc_slot(s + 1) + upoll + ta.z));
                    sts128u<W_TAB + 1536>(l16, uw, (uint32_t)rp, (uint32_t)(rp >> 32), (uint32_t)pn, (uint32_t)(pn >> 32));
                }
                if (__any_sync(0xffffffffu, zero & (k0.y | k1.x | k2.x | k3.x | w0[0].x | w0[1].x | w0[2].x | w0[3].x | w0[4].y | w0[5].y | w0[6].x))) __trap();
                if (__builtin_expect(take(v0, v1, v2, v3), 1)) bar_sync(BR_MB, 256);
                else {
                    do {
                        if (++it > SPIN) __trap();
                        v0 = ld_relaxed4(pp); v1 = ld_relaxed4(pp + 2048); v2 = ld_relaxed4(pp + 16384); v3 = ld_relaxed4(pp + 18432);
                    } while (!take(v0, v1, v2, v3));
                    bar_sync(BR_MB + zero, 256);
                }
                DBG(1);
                float acc[7][4], sa[4], sc[4], sx[4], sy[4];
                uint32_t tb[14];
                auto T = [&](int m, int k) { if (k == 0) mmaqz(acc[m], w0[m], b[0], b[1]); else mmaq(acc[m], wr[m][k - 1], b[2 * k], b[2 * k + 1]); };
                auto TR = [&](int m) { tb[2 * m] = movm(pack_bf16(acc[m][0], acc[m][1])); tb[2 * m + 1] = movm(pack_bf16(acc[m][2], acc[m][3])); };
                auto after = [&](uint32_t v, float dep) { return v ^ (__float_as_uint(dep) & zero); };
                T(6, 0); T(0, 0); T(1, 0); T(2, 0);
                T(6, 1); T(0, 1); T(1, 1); T(3, 0);
                T(6, 2); T(0, 2); T(1, 2); T(2, 1);
                T(6, 3); T(0, 3); T(1, 3); T(3, 1);
                T(6, 4); T(0, 4); T(1, 4); T(2, 2);
                T(6, 5); T(0, 5); T(1, 5); T(3, 2);
                T(6, 6); T(0, 6); T(1, 6); T(2, 3);
                w0[4].x = after(w0[4].x, acc[6][0]); w0[5].x = after(w0[5].x, acc[6][1]);
                const uint32_t ld = after(l16, acc[6][2]);
                uint4 am0 = lds128u<W_MB>(ld, uc);
                const uint2 am3 = lds64u<W_MB + 1536>(ld, uc);
                k0.x = after(k0.x, acc[1][0]);
                DBG(2);
                T(3, 3); T(4, 0); T(5, 0); T(2, 4);
                TR(6); TR(0); TR(1);
                T(3, 4); T(4, 1); T(5, 1); T(2, 5);
                T(3, 5); T(4, 2); T(5, 2); T(2, 6);
                T(3, 6); T(4, 3); T(5, 3);
                am0.x = after(am0.x, acc[2][0]);
                const uint32_t ld2 = after(l16, acc[2][1]);
                uint4 am1 = lds128u<W_MB + 512>(ld2, uc);
                const uint4 am2 = lds128u<W_MB + 1024>(ld2, uc);
                mmaqz(sx, k0, b[0], b[1]); mmaqz(sy, k0, b[2], b[3]);
                T(4, 4); T(5, 4);
                TR(2); TR(3);
                mmaqz(sa, am0, tb[0], tb[2]); mmaqz(sc, am0, tb[1], tb[3]);
                T(4, 5); T(5, 5);
                mmaq(sx, k1, b[4], b[5]); mmaq(sy, k1, b[6], b[7]);
                T(4, 6); T(5, 6);
                mma1688(sa, am3.x, am3.y, tb[12]); mma1688(sc, am3.x, am3.y, tb[13]);
                mmaq(sx, k2, b[8], b[9]); mmaq(sy, k2, b[10], b[11]);
                am1.x = after(am1.x, acc[4][0]);
                TR(4); TR(5);
                mmaq(sa, am1, tb[4], tb[6]); mmaq(sc, am1, tb[5], tb[7]);
                mma1688(sx, k3.x, k3.y, b[12]); mma1688(sy, k3.x, k3.y, b[13]);
                sts64u<W_SMI + 256>(l8, uw, __float_as_uint(sx[0] + sy[2]), __float_as_uint(sx[1] + sy[3]));
                const uint4 ra = lds128u<W_TAB + 1024>(l16, uw);
                bar_arrive((BR_GO + w) ^ (tb[GO_DEP] & zero), 64);
                mmaq(sa, am2, tb[8], tb[10]); mmaq(sc, am2, tb[9], tb[11]);
                sts64u<W_SMI>(l8, uw, __float_as_uint(sa[0] + sc[2]), __float_as_uint(sa[1] + sc[3]));
                DBG(3);
                bar_sync(BR_SM, 128);
                {
                    const float2 p0 = lds64f(sia), p1 = lds64f(sia + WB), p2 = lds64f(sia + 2 * WB), p3 = lds64f(sia + 3 * WB);
                    const float y0 = (p0.x + p1.x) + (p2.x + p3.x), y1 = (p0.y + p1.y) + (p2.y + p3.y);
                    if (w >= 2) { const uint32_t e = pack_bf16(ex2(y0), ex2(y1)); st_async1(ra.x, ra.y, e); st_async1(ra.z, ra.w, e); }
                    else { st_async2(ra.x, ra.y, y0, y1); st_async2(ra.z, ra.w, y0, y1); }
                }
                DBG(4);
                const uint4 tc = lds128u<W_TAB + 512>(l16, uw);
                const uint4 td = lds128u<W_TAB + 1536>(l16, uw);
                const uint32_t va3 = tc.x, ua = tc.y, ua3 = tc.z, ea = tc.w;
                uint2 vb[4][2];
                auto load_v = [&]() {
                    const uint32_t va = stg + uv, va2 = va + 4 * u2;
                    vb[0][0] = lds64u<0>(l8, va); vb[1][0] = lds64u<512>(l8, va); vb[2][0] = lds64u<0>(l8, va2);
                    vb[0][1] = lds64u<256>(l8, va); vb[1][1] = lds64u<768>(l8, va); vb[2][1] = lds64u<256>(l8, va2);
                    vb[3][0] = lds64u<0>(va3, stg); vb[3][1] = lds64u<256>(va3, stg);
                };
                load_v();
                sts128u<W_TB>(l16, uw, tb[0], tb[2], tb[1], tb[3]); sts128u<W_TB + 512>(l16, uw, tb[4], tb[6], tb[5], tb[7]);
                sts128u<W_TB + 1024>(l16, uw, tb[8], tb[10], tb[9], tb[11]); sts64u<W_TB + 1536>(l8, uw, tb[12], tb[13]);
                float o[4][4];
                auto pv_x = [&](const uint4& e01, const uint4& e23) {
#pragma unroll
                    for (int q = 3; q < 7; q++) mmaqz(o[q & 3], e01, vb[q & 3][0].x, vb[q & 3][0].y);
#pragma unroll
                    for (int q = 3; q < 7; q++) mmaq(o[q & 3], e23, vb[q & 3][1].x, vb[q & 3][1].y);
                };
                uint4 u0 = ub, u1 = ub, uu = ub, u3 = ub;
                auto pv_m = [&](float f0, float f1) {
                    const uint4 pm = make_uint4(pack_bf16(f0, f1), __float_as_uint(f0), pack_bf16_again(f0, f1), __float_as_uint(f1));
                    mmaq(o[3], pm, u3.x, u3.y); mmaq(o[0], pm, u0.x, u0.y); mmaq(o[1], pm, u1.x, u1.y); mmaq(o[2], pm, uu.x, uu.y);
                    mmaq(o[3], pm, u3.z, u3.w); mmaq(o[0], pm, u0.z, u0.w); mmaq(o[1], pm, u1.z, u1.w); mmaq(o[2], pm, uu.z, uu.w);
                };
                uint4 res;
                auto finish = [&]() {
                    const float r = rcp(wodd ? o[3][0] : o[3][1]);
                    res = make_uint4(pack_bf16(o[0][0] * r, o[0][1] * r), pack_bf16(o[1][0] * r, o[1][1] * r), pack_bf16(o[2][0] * r, o[2][1] * r),
                                     pack_bf16((wodd ? o[3][1] : o[3][0]) * r, 1.0f));
                };
                mbar_wait_cl(bar + B_SM);
                DBG(5);
                float x0, x1;
                {
                    const uint4 e = ldsm4tu<0>(ea, par);
                    const float2 p0 = lds64fu<R_SMM>(l8, par), p1 = lds64fu<R_SMM + 256>(l8, par), p2 = lds64fu<R_SMM + 512>(l8, par), p3 = lds64fu<R_SMM + 768>(l8, par);
                    x0 = (p0.x + p1.x) + (p2.x + p3.x); x1 = (p0.y + p1.y) + (p2.y + p3.y);
                    pv_x(e, make_uint4(e.y ^ zero, __float_as_uint(x0), e.w ^ zero, __float_as_uint(x1)));
                }
                DBG(6);
                bar_sync(BR_UP, 256);
                u3 = ldsm4q(ua3); u0 = ldsm4q(ua); u1 = ldsm4q(ua + 128); uu = ldsm4u<0>(ua, u2);
                pv_m(ex2(x0), ex2(x1));
                finish();
                if (__builtin_expect(__any_sync(0xffffffffu, __float_as_uint(wodd ? o[3][0] : o[3][1]) - SAFE_LO >= SAFE_SPAN), 0)) {
                    float y[8];
#pragma unroll
                    for (int q = 0; q < 8; q++) {
                        const uint32_t ln = add_here(l8, -sb) >> 3;
                        const uint32_t a = mapa(sb + R_WB + W_SMI + 256 + (2 * (ln & 3) + (q & 1)) * 32 + (ln >> 2) * 4, rk + (q >> 1));
                        y[q] = (ldr32f(a) + ldr32f(a + WB)) + (ldr32f(a + 2 * WB) + ldr32f(a + 3 * WB));
                    }
                    float m = fmaxf(x0, x1);
#pragma unroll
                    for (int q = 0; q < 8; q++) m = fmaxf(m, y[q]);
                    m = fmaxf(m, __shfl_xor_sync(0xffffffffu, m, 1)); m = fmaxf(m, __shfl_xor_sync(0xffffffffu, m, 2));
                    load_v();
                    pv_x(make_uint4(pack_bf16(ex2(y[0] - m), ex2(y[1] - m)), 0u, pack_bf16(ex2(y[2] - m), ex2(y[3] - m)), 0u),
                         make_uint4(pack_bf16(ex2(y[4] - m), ex2(y[5] - m)), 0u, pack_bf16(ex2(y[6] - m), ex2(y[7] - m)), 0u));
                    pv_m(ex2(x0 - m), ex2(x1 - m));
                    finish();
                }
                DBG(8);
                red_bf16x8((void*)(((uint64_t)td.y << 32) | td.x), res.x, res.y, res.z, res.w);
                t0 = clk();
                DBG(9);
                bar_arrive(BR_RED, 256);
                SCHED_FENCE(zero, 5);
                pp = (const uint8_t*)(((uint64_t)td.w << 32) | td.z);
                ub = make_uint4(hsum4(u0.x, u0.y, u0.z, u0.w), hsum4(u1.x, u1.y, u1.z, u1.w), hsum4(uu.x, uu.y, uu.z, uu.w), hsum4(u3.x, u3.y, u3.z, u3.w));
            }
            bar_arrive(BR_POLL + w, 64);
            put_u(NSEG - 1);
            bar_arrive(BR_PRO, 160);
        } else {
            const int lane = fresh_lane(), g = lane >> 2, t = lane & 3;
            const uint32_t l16 = sb + lane * 16, l8 = sb + lane * 8, wsa = l16 + R_WB + wid * WB;
            uint4 wr[7][6];
            load_weights(wr, lane);
            uint32_t* pdst = g_P + (h * 14 + (c * (c + 3) >> 1)) * 32 + lane;
            const uint32_t xa = sb + S_X + (lane & 15) * 240;
            auto softmax_rows = [&](int sl, bool gate) {
                mbar_wait_cl(sb + R_BAR + B_LS + sl * 8);
                const uint32_t a = R_LS + (sl & 1) * 5120;
                const float4 q0 = sum4(lds128f(l16 + a), lds128f(l16 + a + 1280), lds128f(l16 + a + 2560), lds128f(l16 + a + 3840));
                float4 q1 = make_float4(0.f, 0.f, 0.f, 0.f);
                q1 = sum4(lds128f(l16 + a + 512), lds128f(l16 + a + 1792), lds128f(l16 + a + 3072), lds128f(l16 + a + 4352));
                const float2 p0 = lds64f(l8 + a + 1024), p1 = lds64f(l8 + a + 2304), p2 = lds64f(l8 + a + 3584), p3 = lds64f(l8 + a + 4864);
                float v[10] = {q0.x, q0.y, q0.z, q0.w, q1.x, q1.y, q1.z, q1.w, (p0.x + p1.x) + (p2.x + p3.x), (p0.y + p1.y) + (p2.y + p3.y)};
                const int lim = 8 * c + g - 2 * t;
#pragma unroll
                for (int i = 0; i < 8; i++) v[i] = (8 * (i >> 1) + (i & 1) <= lim) ? v[i] : -INFINITY;
                float e[10], l[4];
                auto expo = [&](float m) {
#pragma unroll
                    for (int i = 0; i < 10; i++) e[i] = ex2(v[i] - m);
                    mma16816z(l, pack_bf16(e[0], e[1]), pack_bf16(e[4], e[5]), pack_bf16(e[2], e[3]), pack_bf16(e[6], e[7]), ONE2, ONE2);
                    mma1688(l, pack_bf16(e[8], e[9]), 0u, ONE2);
                    l[0] += l[2];
                };
                expo(0.f);
                if (__builtin_expect(__any_sync(0xffffffffu, __float_as_uint(l[0]) - SAFE_LO >= SAFE_SPAN), 0)) {
                    float m = v[0];
#pragma unroll
                    for (int i = 1; i < 10; i++) m = fmaxf(m, v[i]);
                    m = fmaxf(m, __shfl_xor_sync(0xffffffffu, m, 1)); m = fmaxf(m, __shfl_xor_sync(0xffffffffu, m, 2));
                    expo(m);
                }
                const float r = rcp(l[0]);
                uint32_t* pd = pdst + (sl & (RS - 1)) * (16 * 448);
                if (gate) bar_sync((BR_POLL + w) ^ (__float_as_uint(r) & zero), 64);
#pragma unroll
                for (int q = 0; q < 4; q++) if (q <= c) pd[q * 32] = pack_bf16(e[2 * q] * r, e[2 * q + 1] * r);
                pd[(c + 1) * 32] = pack_bf16(e[8] * r, e[9] * r);
            };
            auto publish = [&](int sl) {
                __syncwarp();
                if (lane == 0) mbar_arrive(sb + R_BAR + B_PUB + sl * 8);
                if (sl >= 2) mbar_wait(sb + R_BAR + B_Z + (sl - 2) * 8, 0);
            };
            bar_sync(BR_POLL + w, 64);
#pragma unroll 1
            for (int s = 0; s < NSEG; s++) {
                const uint32_t stg = R_STG + (s & 3) * STGB;
                uint4 w0[7];
#pragma unroll
                for (int m = 0; m < 7 - UW0; m++) w0[m] = lds128(wsa + m * 512);
                bar_sync(BR_MB, 256);
                mbar_arrive_if(lane + w == 0, sb + R_BAR + B_H + s * 8);
                const uint32_t ba = wsa - 4 * WB + W_MB;
                const uint4 b0 = lds128(ba), b1 = lds128(ba + 512), b2 = lds128(ba + 1024);
                const uint2 b3 = lds64(ba + 1536);
#pragma unroll
                for (int m = 7 - UW0; m < 7; m++) w0[m] = lds128(wsa + m * 512);
                bar_sync(BR_GO + w, 64);
                SCHED_FENCE(zero, 2);
                DBG(11);
                float acc[7][4];
                const uint32_t b[14] = {b0.x, b0.y, b0.z, b0.w, b1.x, b1.y, b1.z, b1.w, b2.x, b2.y, b2.z, b2.w, b3.x, b3.y};
                auto U = [&](int m, int k) { if (k == 0) mmaqz(acc[m], w0[m], b[0], b[1]); else mmaq(acc[m], wr[m][k - 1], b[2 * k], b[2 * k + 1]); };
#pragma unroll
                for (int k = 0; k < 7; k++)
#pragma unroll
                    for (int m = 0; m < 7; m++) U(m, k);
                {
                    const uint32_t a = wsa + W_UP;
#pragma unroll
                    for (int q = 0; q < 3; q++)
                        stsm4(a + q * 512, make_uint4(pack_bf16(acc[2 * q][0], acc[2 * q][1]), pack_bf16(acc[2 * q][2], acc[2 * q][3]),
                                                      pack_bf16(acc[2 * q + 1][0], acc[2 * q + 1][1]), pack_bf16(acc[2 * q + 1][2], acc[2 * q + 1][3])));
                    stsm2(a + 1536, pack_bf16(acc[6][0], acc[6][1]), pack_bf16(acc[6][2], acc[6][3]));
                }
                bar_arrive(BR_UP, 256);
                DBG(12);
                bar_sync(BR_RED, 256);
                if (w == 1) { if (s > 0) softmax_rows(s - 1, true); else bar_sync(BR_POLL + w, 64); }
                else {
                    const uint32_t dst = R_LS + (s & 1) * 5120 + c * 1280, lb = R_BAR + B_LS + s * 8;
                    const uint32_t xs = xa + stg + (lane >> 4) * 32, x6 = xa + stg + (lane >> 4) * 16 + 192;
                    const uint32_t r0 = mapa(sb, rk), r1 = mapa(sb, rk + 1), r2 = mapa(sb, rk + 2), r3 = mapa(sb, rk + 3);
                    auto X = [&](int mt, int k) { return ldsm4q(k == 6 ? x6 + mt * 3840 : xs + mt * 3840 + (k >> 1) * 64 + (k & 1) * 16); };
                    float y[4][4];
                    if (w == 0) {
                        uint32_t f[14];
#pragma unroll
                        for (int q = 0; q < 3; q++) {
                            const uint32_t a = l16 + R_WB + W_TB + q * 512;
                            const uint4 p0 = lds128(a), p1 = lds128(a + WB), p2 = lds128(a + 2 * WB), p3 = lds128(a + 3 * WB);
                            f[4 * q] = hsum4(p0.x, p1.x, p2.x, p3.x); f[4 * q + 1] = hsum4(p0.y, p1.y, p2.y, p3.y);
                            f[4 * q + 2] = hsum4(p0.z, p1.z, p2.z, p3.z); f[4 * q + 3] = hsum4(p0.w, p1.w, p2.w, p3.w);
                        }
                        const uint32_t a = l8 + R_WB + W_TB + 1536;
                        const uint2 p0 = lds64(a), p1 = lds64(a + WB), p2 = lds64(a + 2 * WB), p3 = lds64(a + 3 * WB);
                        f[12] = hsum4(p0.x, p1.x, p2.x, p3.x); f[13] = hsum4(p0.y, p1.y, p2.y, p3.y);
#pragma unroll
                        for (int k = 0; k < 7; k++)
#pragma unroll
                            for (int mt = 0; mt < 2; mt++) {
                                if (k < 2) mmaqz(y[2 * mt + k], X(mt, k), f[2 * k], f[2 * k + 1]); else mmaq(y[2 * mt + (k & 1)], X(mt, k), f[2 * k], f[2 * k + 1]);
                            }
                        const uint32_t o = dst + 1024 + lane * 8;
                        bar_sync((BR_POLL + w) ^ (__float_as_uint(y[2][0]) & zero), 64);
                        st_async2(r0 + o, r0 + lb, y[0][0] + y[1][0], y[0][1] + y[1][1]); st_async2(r1 + o, r1 + lb, y[0][2] + y[1][2], y[0][3] + y[1][3]);
                        st_async2(r2 + o, r2 + lb, y[2][0] + y[3][0], y[2][1] + y[3][1]); st_async2(r3 + o, r3 + lb, y[2][2] + y[3][2], y[2][3] + y[3][3]);
                    } else {
                        const uint32_t ka = stg + S_KS + (w == 3 ? 3584 : 0);
                        uint32_t f[2][14];
#pragma unroll
                        for (int j = 0; j < 2; j++) {
#pragma unroll
                            for (int q = 0; q < 3; q++) { const uint4 v = lds128(l16 + ka + j * 1792 + q * 512); f[j][4 * q] = v.x; f[j][4 * q + 1] = v.y; f[j][4 * q + 2] = v.z; f[j][4 * q + 3] = v.w; }
                            const uint2 v = lds64(l8 + ka + j * 1792 + 1536); f[j][12] = v.x; f[j][13] = v.y;
                        }
                        if (w == 2) {
#pragma unroll
                            for (int k = 0; k < 7; k++)
#pragma unroll
                                for (int mt = 0; mt < 2; mt++) {
                                    const uint4 a = X(mt, k);
                                    if (k == 0) { mmaqz(y[2 * mt], a, f[0][0], f[0][1]); mmaqz(y[2 * mt + 1], a, f[1][0], f[1][1]); }
                                    else { mmaq(y[2 * mt], a, f[0][2 * k], f[0][2 * k + 1]); mmaq(y[2 * mt + 1], a, f[1][2 * k], f[1][2 * k + 1]); }
                                }
                            const uint32_t o = dst + lane * 16;
                            bar_sync((BR_POLL + w) ^ (__float_as_uint(y[3][0]) & zero), 64);
                            st_async4(r0 + o, r0 + lb, y[0][0], y[0][1], y[1][0], y[1][1]); st_async4(r1 + o, r1 + lb, y[0][2], y[0][3], y[1][2], y[1][3]);
                            st_async4(r2 + o, r2 + lb, y[2][0], y[2][1], y[3][0], y[3][1]); st_async4(r3 + o, r3 + lb, y[2][2], y[2][3], y[3][2], y[3][3]);
                        } else {
#pragma unroll
                            for (int k = 0; k < 7; k++) {
                                const uint4 a = X(1, k);
                                if (k < 2) { mmaqz(y[k], a, f[0][2 * k], f[0][2 * k + 1]); mmaqz(y[2 + k], a, f[1][2 * k], f[1][2 * k + 1]); }
                                else { mmaq(y[k & 1], a, f[0][2 * k], f[0][2 * k + 1]); mmaq(y[2 + (k & 1)], a, f[1][2 * k], f[1][2 * k + 1]); }
                            }
                            const uint32_t o = dst + 512 + lane * 16;
                            bar_sync((BR_POLL + w) ^ (__float_as_uint(y[2][0]) & zero), 64);
                            st_async4(r2 + o, r2 + lb, y[0][0] + y[1][0], y[0][1] + y[1][1], y[2][0] + y[3][0], y[2][1] + y[3][1]);
                            st_async4(r3 + o, r3 + lb, y[0][2] + y[1][2], y[0][3] + y[1][3], y[2][2] + y[3][2], y[2][3] + y[3][3]);
                        }
                    }
                }
                DBG(13);
                if (w == 1 && s > 0) publish(s - 1);
                DBG(14);
            }
            if (w == 1) softmax_rows(NSEG - 1, false);
            if (w == 1) { bar_sync(BR_PRO, 160); publish(NSEG - 1); }
        }
        cluster_sync();
    } else {
        asm volatile("setmaxnreg.dec.sync.aligned.u32 24;");
        const unsigned epoch = lds32(sb + R_MISC);
        const int lane = fresh_lane();
        if (w == 0) {
            wait_count_warp(&g_INIT, (epoch + 1) * 64, 100);
            fence_gpu();
            bar_sync(BR_ALL, 288);
            asm volatile("barrier.cluster.arrive.relaxed.aligned;" ::: "memory");
            const unsigned* ft = g_FT + (lane < 2 ? 2 * h + lane : 32 + 2 * h + (c >> 1)) * 32;
#pragma unroll 1
            for (int seg = 0; seg < NSEG; seg++) {
                if (!(seg & 1)) {
                    wait_count_warp(ft + (~(seg >> 1) & 1), epoch * 32 + (((seg >> 1) + 9) >> 1), seg ? 0 : 40);
                    fence_gpu();
                    asm volatile("fence.proxy.async.global;" ::: "memory");
                }
                const uint32_t bar = sb + R_BAR + B_KV + seg * 8, dst = sb + R_STG + (seg & 3) * STGB;
                const uint8_t* kp = g_K + ((seg & (RS - 1)) * 16 + h) * 28672;
                const uint8_t* vp = g_V + (((seg & (RS - 1)) * 16 + h) * 4 + c) * 7168;
                if (lane == 0 && seg == 0) GT(0, 7);
                if (seg >= 2) mbar_wait(sb + R_BAR + B_H + (seg - 2) * 8, 0);
                if (elect_one()) {
                    bulk_g2s(dst + S_KO, kp + c * 7168, 7168, bar);
                    bulk_g2s(dst + S_V, vp, 7168, bar);
                    tma2d(dst + S_X, &mapXs, 112 * c, 32 * seg, bar);
#pragma unroll
                    for (int j = 0; j < XXN; j++) bulk_g2s(dst + S_KS + j * 1792, kp + j * 7168 + c * 1792, 1792, bar);
                }
                if (lane == 0 && seg == 2) GT(0, 4);
                if (lane == 0 && seg == NSEG - 1) GT(0, 5);
                if (seg == 1) asm volatile("barrier.cluster.wait.aligned;" ::: "memory");
            }
        } else if (w == 1) {
            cluster_sync();
            if (lane == 0) GT(0, 3);
            uint8_t* zp = accb + acc_off(c, h >> 2, (h & 3) * 8 + (lane & 7));
#pragma unroll 1
            for (int seg = 0; seg < NSEG; seg++) {
                mbar_wait(sb + R_BAR + B_PUB + seg * 8, 0);
                if (lane < 8 && seg < NSEG - 8) *(uint4*)(zp + acc_slot(seg)) = make_uint4(0, 0, 0, 0);
                __syncwarp();
                if (lane == 0) {
                    fence_gpu();
                    red_inc(g_CNT + seg * 32); mbar_arrive(sb + R_BAR + B_Z + seg * 8); }
                __syncwarp();
            }
            if (lane == 0) GT(0, 6);
        } else cluster_sync();
        cluster_sync();
        if (w == 1 && lane == 0) red_inc(&g_EXIT);
    }
}

constexpr int BLK = 28672;
constexpr int G_RING = 7 * BLK;
constexpr int G_BAR = G_RING + 7 * 4096;
constexpr int G_PUB = G_BAR + 18 * 8;
constexpr int G_RDY = G_PUB + 39 * 8;
constexpr int G_MISC = G_RDY + 7 * 8;
constexpr int G_SMEM = G_MISC + 16;
static_assert(G_SMEM <= 232448, "smem");
#define PACE 120
constexpr int LAG = 4;
static_assert(LAG + 3 <= RS / 2, "ring");

template <int NSTG, class F>
__device__ __forceinline__ void tile_mainloop(float* d, uint32_t sb, int slot, uint32_t par, uint64_t db, uint32_t kstep, bool trans,
                                              bool lead, int pass_to, bool wait_b, F step) {
    const uint64_t da0 = sdesc(sb + G_RING, 16, 512, 2);
    int prev = 0;
#pragma unroll
    for (int i = 0; i < NSTG; i++) {
        if (!(i & 1) && wait_b) mbar_wait(sb + G_BAR + (14 + (i >> 1)) * 8, 0);
        mbar_wait(sb + G_BAR + slot * 8, par);
        wg_fence();
        const uint64_t da = da0 + slot * 256, b0 = db + (i >> 1) * (BLK >> 4) + (i & 1) * 2 * kstep;
        if (trans) { wgmma224<1>(d, da, b0, i); wgmma224<1>(d, da + 2, b0 + kstep, 1); }
        else { wgmma224<0>(d, da, b0, i); wgmma224<0>(d, da + 2, b0 + kstep, 1); }
        wg_commit();
        if (i == NSTG - 1 && pass_to) bar_arrive(pass_to, 256);
        step(i);
        if (i > 0) { wg_wait<1>(); mbar_arrive_if(lead, sb + G_BAR + (7 + prev) * 8); }
        prev = slot;
        if (++slot == 7) { slot = 0; par ^= 1; }
    }
    wg_wait<0>();
    mbar_arrive_if(lead, sb + G_BAR + (7 + prev) * 8);
}

template <int M>
__device__ __forceinline__ void fold_role(uint32_t sb, int n, int wg, int u, int lane) {
    const bool lead = lane == 0;
    const uint64_t db = M == 0 ? sdesc(sb + 3 * BLK, 16, 1024, 1) : sdesc(sb + 3 * BLK, 4096, 512, 2);
    const uint32_t sa = sb + (8 * ((lane >> 3) & 1) + (lane & 7)) * 128 + (((2 * u + (lane >> 4)) ^ (lane & 7)) << 4);
    uint4* dst = g_F + (n * 56 + 4 * wg + u) * 224 + lane;
    uint4 q[14], qa[14];
#pragma unroll
    for (int i = 0; i < 14; i++) q[i] = make_uint4(0, 0, 0, 0);
    int blk = wg;
#pragma unroll 1
    for (;; blk += 2, dst += 8 * 224) {
        float d[112];
        bar_sync(1 + wg, 256);
        tile_mainloop<8>(d, sb, blk, blk & 1, db, M == 0 ? 2 : 64, M == 1, lead, 2 - wg, blk < 2,
                         [&](int i) { if (i < 7 && blk >= 2) dst[(28 - 8) * 224 + i * 32] = q[7 + i]; });
        if (u == 0 && lead) GT(1, 6 + blk);
        if (blk >= 2) { __syncwarp(); mbar_arrive_if(lead, sb + G_PUB + (blk - 2) * 8); }
        const float sc = M ? 1.f : 0.0625f * LOG2E;
#pragma unroll
        for (int i = 0; i < 14; i++) {
            const float* e = d + 8 * i;
            qa[i] = q[i];
            q[i] = make_uint4(movm(pack_bf16(e[0] * sc, e[1] * sc)), movm(pack_bf16(e[4] * sc, e[5] * sc)),
                              movm(pack_bf16(e[2] * sc, e[3] * sc)), movm(pack_bf16(e[6] * sc, e[7] * sc)));
        }
        if (blk >= 5) break;
        if (blk < 3) {
#pragma unroll
            for (int i = 0; i < 14; i++) stsm4(sa + blk * BLK + i * 2048, q[i]);
        }
#pragma unroll
        for (int i = 0; i < 7; i++) dst[i * 32] = q[i];
    }
    auto to_global = [&]() {
#pragma unroll
        for (int i = 0; i < 14; i++) dst[(i / 7) * (28 * 224) + (i % 7) * 32] = q[i];
        __syncwarp();
        mbar_arrive_if(lead, sb + G_PUB + blk * 8);
    };
    if (wg == 1) to_global();
    bar_sync(3, 256);
#pragma unroll
    for (int i = 0; i < 14; i++) { stsm4(sa + (blk - 2) * BLK + i * 2048, qa[i]); stsm4(sa + blk * BLK + i * 2048, q[i]); }
    asm volatile("fence.proxy.async.shared::cta;" ::: "memory");
    bar_sync(3, 256);
    if (wg == 0 && u == 0 && lead) GT(1, 13);
    if (wg == 0) to_global();
}

__device__ __forceinline__ void bulk_consumer(uint32_t sb, int n, unsigned epoch, __nv_bfloat16* __restrict__ out, int phases) {
    const int lane = fresh_lane(), wid = __shfl_sync(0xffffffffu, threadIdx.x >> 5, 0), wg = wid >> 2, u = wid & 3;
    const int h = (n >> 1) & 15, hf = n & 1;
    const bool lead = lane == 0;
    if (phases & 1) {
        if (wg == 1) bar_arrive(1, 256);
        if (n < 32) fold_role<0>(sb, n, wg, u, lane); else fold_role<1>(sb, n, wg, u, lane);
        bar_sync(1 + wg, 256);
    }
    const uint64_t db = sdesc(sb, 16, 1024, 1);
    float acc[2][2][4];
    int unit = n, done = -1;
#pragma unroll 1
    for (int tile = 1 - wg; tile < LAG + 36; tile += 2) {
        if (tile < 32 && (phases & 1)) {
            const int seg = 2 * tile + (u >> 1), slot = seg & (RS - 1);
            float d[112];
            tile_mainloop<14>(d, sb, 0, 0, db, 2, false, lead, tile == 31 ? 0 : 2 - wg, false, [](int) {});
            if (tile >= RS / 2) {
                if (n < 32) wait_count_warp(g_CNT + (2 * tile + 1 - RS) * 32, (epoch + 1) * 64, 100);
                else wait_count_warp(g_WD + (tile - RS / 2) * 32, (epoch + 1) * 56, 100);
            }
            uint32_t t0 = clk();
            auto pace = [&]() { if (PACE && tile > 1) { uint32_t t1; do { t1 = clk(); } while ((int)(t1 - t0) < 0); t0 = t1 + PACE; } };
            if (n < 32) {
                uint8_t* rec = g_K + (((slot * 16 + h) * 4 + 2 * (u & 1)) * 4 + 2 * hf) * 1792;
#pragma unroll
                for (int wq = 0; wq < 2; wq++) {
#pragma unroll
                    for (int q = 0; q < 3; q++) {
                        const float* e = d + 56 * wq + 16 * q;
                        pace();
                        *(uint4*)(rec + wq * 1792 + q * 512 + lane * 16) = make_uint4(pack_bf16(e[0], e[1]), pack_bf16(e[8], e[9]), pack_bf16(e[4], e[5]), pack_bf16(e[12], e[13]));
                        pace();
                        *(uint4*)(rec + 7168 + wq * 1792 + q * 512 + lane * 16) = make_uint4(pack_bf16(e[2], e[3]), pack_bf16(e[10], e[11]), pack_bf16(e[6], e[7]), pack_bf16(e[14], e[15]));
                    }
                    const float* e = d + 56 * wq + 48;
                    pace();
                    *(uint2*)(rec + wq * 1792 + 1536 + lane * 8) = make_uint2(pack_bf16(e[0], e[1]), pack_bf16(e[4], e[5]));
                    *(uint2*)(rec + 7168 + wq * 1792 + 1536 + lane * 8) = make_uint2(pack_bf16(e[2], e[3]), pack_bf16(e[6], e[7]));
                }
            } else {
                uint8_t* rec = g_V + ((slot * 16 + h) * 56 + 28 * hf) * 512 + (u & 1) * 256 + lane * 8;
#pragma unroll
                for (int i = 0; i < 28; i++) {
                    if (!(i & 1)) pace();
                    *(uint2*)(rec + i * 512) = make_uint2(movm(pack_bf16(d[4 * i], d[4 * i + 1])), movm(pack_bf16(d[4 * i + 2], d[4 * i + 3])));
                }
            }
            __syncwarp();
            mbar_arrive_if(lead, sb + G_PUB + (7 + tile) * 8);
        }
        if (done >= 0) {
            uint32_t* o = (uint32_t*)(out + (size_t)(done / 7 * 32 + (lane >> 2)) * OUTW + D + 64 * (done % 7) + 16 * u) + (lane & 3);
#pragma unroll
            for (int r = 0; r < 4; r++)
#pragma unroll
                for (int j = 0; j < 2; j++) o[r * (8 * OUTW / 2) + 4 * j] = pack_bf16(acc[r >> 1][j][2 * (r & 1)], acc[r >> 1][j][2 * (r & 1) + 1]);
            done = -1;
        }
        while (LAG + unit / 14 + 2 < tile) unit += 64;
        const int half = tile - (LAG + unit / 14);
        const bool turn = tile < 30 && (phases & 1);
        if (unit < NSEG * 7 && (half == 0 || half == 2) && (phases & 2)) {
            if (half == 0) mbar_wait(sb + G_RDY + (unit >> 6) * 8, 0);
            const int sh = ((unit / 7) & (RS - 1)) * 16 + 4 * half, tl = 8 * (unit % 7) + 2 * u;
            const uint8_t* vp = g_V + (sh * 56 + tl) * 512 + lane * 8;
            const uint32_t* up = g_U + (sh * 56 + tl) * 32 + lane;
            const uint32_t* pp = g_P + sh * 448 + lane;
            uint2 v[8][4]; uint32_t p[8][14], m[8][2];
#pragma unroll
            for (int j = 0; j < 8; j++) {
#pragma unroll
                for (int i = 0; i < 4; i++) v[j][i] = __ldcg((const uint2*)(vp + j * (56 * 512) + i * 256));
#pragma unroll
                for (int i = 0; i < 14; i++) p[j][i] = __ldca(pp + j * 448 + i * 32);
                m[j][0] = __ldcg(up + j * (56 * 32)); m[j][1] = __ldcg(up + j * (56 * 32) + 32);
            }
            if (half == 0) {
#pragma unroll
                for (int i = 0; i < 16; i++) (&acc[0][0][0])[i] = 0.f;
            }
            if (turn) bar_sync(1 + wg, 256);
#pragma unroll
            for (int j = 0; j < 8; j++) {
                const uint32_t* q = p[j];
#pragma unroll
                for (int i = 0; i < 2; i++) {
                    mma16816(acc[0][i], q[0], q[2], 0u, q[3], v[j][2 * i].x, v[j][2 * i].y);
                    mma16816(acc[1][i], q[5], q[9], q[6], q[10], v[j][2 * i].x, v[j][2 * i].y);
                }
#pragma unroll
                for (int i = 0; i < 2; i++) { mma1688(acc[0][i], q[1], q[4], m[j][i]); mma16816(acc[1][i], q[7], q[11], 0u, q[12], v[j][2 * i + 1].x, v[j][2 * i + 1].y); }
#pragma unroll
                for (int i = 0; i < 2; i++) mma1688(acc[1][i], q[8], q[13], m[j][i]);
            }
            if (half == 2) { done = unit; if (lead) red_inc(g_WD + (unit / 14) * 32 + (__float_as_uint(acc[1][1][0]) & (phases >> 8))); }
        } else if (turn) bar_sync(1 + wg, 256);
    }
}

__global__ void __launch_bounds__(384, 1)
k_bulk(const __grid_constant__ CUtensorMap mapX, const __grid_constant__ CUtensorMap mapK, const __grid_constant__ CUtensorMap mapV,
       const __grid_constant__ CUtensorMap mapQ, const __grid_constant__ CUtensorMap mapO, __nv_bfloat16* __restrict__ out, unsigned ntotal, int phases) {
    extern __shared__ __align__(1024) uint8_t smem[];
    const uint32_t sb = smem_u32(smem);
    const int n = blockIdx.x, wid = __shfl_sync(0xffffffffu, threadIdx.x >> 5, 0);
    if (threadIdx.x == 0) GT(1, 0);
    if (wid == 8 && elect_one()) {
        for (int i = 0; i < 7; i++) { mbar_init(sb + G_BAR + i * 8, 1); mbar_init(sb + G_BAR + (7 + i) * 8, 4); }
        for (int i = 0; i < 4; i++) mbar_init(sb + G_BAR + (14 + i) * 8, 1);
        asm volatile("fence.mbarrier_init.release.cluster;" ::: "memory");
        asm volatile("fence.proxy.async.shared::cta;" ::: "memory");
        if (n < 64 && (phases & 1)) {
            const int h = (n >> 1) & 15, hf = n & 1;
            for (int i = 0; i < 4; i++) {
                const uint32_t bar = sb + G_BAR + (14 + i) * 8;
                mbar_expect(bar, BLK);
                if (n < 32) tma2d(sb + (3 + i) * BLK, &mapQ, h * DH + 64 * i, 224 * hf, bar);
                else tma3d(sb + (3 + i) * BLK, &mapO, 0, h * DH + 64 * i, 7 * hf, bar);
            }
        }
    }
    if (threadIdx.x < 46) mbar_init(sb + G_PUB + threadIdx.x * 8, threadIdx.x < 39 ? 4 : 1);
    if (threadIdx.x == 64) sts32(sb + G_MISC, ld_relaxed(&g_EXIT) / ntotal);
    __syncthreads();
    if (wid < 8) {
        asm volatile("setmaxnreg.inc.sync.aligned.u32 240;");
        if (n < 64) bulk_consumer(sb, n, lds32(sb + G_MISC), out, phases);
        if (wid == 0 && elect_one()) GT(1, 5);
    } else {
        asm volatile("setmaxnreg.dec.sync.aligned.u32 24;");
        const unsigned epoch = lds32(sb + G_MISC);
        if (wid == 9 && elect_one()) red_inc(&g_EXIT);
        if (n < 64) {
            if (wid == 8) {
                if (phases & 1) {
                    const int h = (n >> 1) & 15;
                    int slot = 0; uint32_t par = 1;
#pragma unroll 1
                    for (int tile = 0; tile < 39; tile++) {
                        const CUtensorMap* map = tile >= 7 ? &mapX : (n < 32 ? &mapK : &mapV);
                        const int x0 = tile >= 7 ? 0 : h * DH, y = 64 * (tile >= 7 ? tile - 7 : tile), ns = tile >= 7 ? 14 : 8;
#pragma unroll 1
                        for (int i = 0; i < ns; i++) {
                            mbar_wait(sb + G_BAR + (7 + slot) * 8, par);
                            if (elect_one()) {
                                mbar_expect(sb + G_BAR + slot * 8, 4096);
                                tma2d(sb + G_RING + slot * 4096, map, x0 + 32 * i, y, sb + G_BAR + slot * 8);
                            }
                            if (++slot == 7) { slot = 0; par ^= 1; }
                        }
                    }
                }
            } else if (wid == 9) {
                if (phases & 2) {
#pragma unroll 1
                    for (int k = 0; k < 7; k++) {
                        wait_count_warp(g_CNT + ((n + 64 * k) / 7) * 32, (epoch + 1) * 64, k < 6 ? 200 : 20);
                        fence_gpu();
                        if (elect_one()) mbar_arrive(sb + G_RDY + k * 8);
                    }
                }
            } else if (phases & 1) {
#pragma unroll 1
                for (int q = wid - 10; q < 39; q += 2) {
                    mbar_wait(sb + G_PUB + q * 8, 0);
                    fence_gpu();
                    if (elect_one()) {
                        st_relaxed(g_FT + n * 32 + (q & 1), epoch * 32 + (q >> 1) + 1);
                        if (q == 6) GT(1, 2);
                        if (q == 7) GT(1, 3);
                    }
                }
            }
        }
    }
}

}

extern "C" void kernel_launch(void* const* d_in, const int* in_sizes, int n_in, void* d_out, int out_size) {
    typedef const __nv_bfloat16* bp;
    __nv_bfloat16* out = (__nv_bfloat16*)d_out;
    const SsmArgs ssm = {(bp)d_in[0], (bp)d_in[1], (bp)d_in[2], (bp)d_in[3], (bp)d_in[4], (bp)d_in[5], (bp)d_in[6], out};
    const bp x = (bp)d_in[7], mem0 = (bp)d_in[8];
    static int nsm = 0;
    typedef CUresult (*EncodeFn)(CUtensorMap*, CUtensorMapDataType, cuuint32_t, void*, const cuuint64_t*, const cuuint64_t*, const cuuint32_t*,
                                 const cuuint32_t*, CUtensorMapInterleave, CUtensorMapSwizzle, CUtensorMapL2promotion, CUtensorMapFloatOOBfill);
    static EncodeFn encode = nullptr;
    if (!nsm) {
        cudaFuncSetAttribute(k_rec, cudaFuncAttributeMaxDynamicSharedMemorySize, R_SMEM);
        cudaFuncSetAttribute(k_rec, cudaFuncAttributeNonPortableClusterSizeAllowed, 1);
        cudaFuncSetAttribute(k_bulk, cudaFuncAttributeMaxDynamicSharedMemorySize, G_SMEM);
        int dev = 0; cudaGetDevice(&dev);
        cudaDeviceGetAttribute(&nsm, cudaDevAttrMultiProcessorCount, dev);
        cudaDriverEntryPointQueryResult qr;
        cudaGetDriverEntryPoint("cuTensorMapEncodeTiled", (void**)&encode, cudaEnableDefault, &qr);
    }
    auto make_map = [&](const void* p, int rank, cuuint64_t d0, cuuint64_t d1, cuuint64_t d2, cuuint64_t s1, cuuint64_t s2,
                        cuuint32_t b0, cuuint32_t b1, cuuint32_t b2, CUtensorMapSwizzle sw) {
        CUtensorMap m;
        const cuuint64_t dims[3] = {d0, d1, d2}, strides[2] = {s1, s2};
        const cuuint32_t box[3] = {b0, b1, b2}, es[3] = {1, 1, 1};
        encode(&m, CU_TENSOR_MAP_DATA_TYPE_BFLOAT16, rank, (void*)p, dims, strides, box, es, CU_TENSOR_MAP_INTERLEAVE_NONE,
               sw, CU_TENSOR_MAP_L2_PROMOTION_L2_128B, CU_TENSOR_MAP_FLOAT_OOB_FILL_NONE);
        return m;
    };
    const CUtensorMap mapX = make_map(x, 2, D, S, 1, D * 2, 0, 32, 64, 1, CU_TENSOR_MAP_SWIZZLE_64B);
    const CUtensorMap mapXs = make_map(x, 2, D, S, 1, D * 2, 0, 120, 32, 1, CU_TENSOR_MAP_SWIZZLE_NONE);
    const CUtensorMap mapQ = make_map(d_in[9], 2, 4096, D, 1, 8192, 0, 64, 224, 1, CU_TENSOR_MAP_SWIZZLE_128B);
    const CUtensorMap mapK = make_map(d_in[10], 2, 4096, D, 1, 8192, 0, 32, 64, 1, CU_TENSOR_MAP_SWIZZLE_64B);
    const CUtensorMap mapV = make_map(d_in[11], 2, 4096, D, 1, 8192, 0, 32, 64, 1, CU_TENSOR_MAP_SWIZZLE_64B);
    const CUtensorMap mapO = make_map(d_in[12], 3, 32, 4096, 14, D * 2, 64, 32, 64, 7, CU_TENSOR_MAP_SWIZZLE_64B);
    const int nbulk = nsm - 64;
    k_rec<<<64, 384, R_SMEM, cudaStreamPerThread>>>(mapXs, ssm, (const uint8_t*)x, mem0, (const uint8_t*)d_in[9], (const uint8_t*)d_in[10],
                                                    (const uint8_t*)d_in[11], (const uint8_t*)d_in[12], (unsigned)(64 + nbulk), 0u);
    cudaLaunchAttribute pdl[1];
    pdl[0].id = cudaLaunchAttributeProgrammaticStreamSerialization;
    pdl[0].val.programmaticStreamSerializationAllowed = 1;
    cudaLaunchConfig_t cfg = {};
    cfg.stream = cudaStreamPerThread;
    cfg.attrs = pdl; cfg.numAttrs = 1;
    cfg.gridDim = dim3(nbulk); cfg.blockDim = dim3(384); cfg.dynamicSmemBytes = G_SMEM;
    cudaLaunchKernelEx(&cfg, k_bulk, mapX, mapK, mapV, mapQ, mapO, out, (unsigned)(64 + nbulk), 3);
}
```

```cpp
#include <cuda.h>
#include <cuda_runtime.h>
#include <cuda_bf16.h>
#include <cuda_fp16.h>
#include <stdint.h>
#include <string.h>

namespace {

constexpr int D = 448, S = 2048, NSEG = 64, DH = 256, NST = 256, OUTW = 896;
constexpr int RS = 16;

__device__ uint4 g_F[2 * 16 * 4 * 28 * 7 * 32];
__device__ __align__(128) uint8_t g_K[RS * 16 * 4 * 4 * 1792];
__device__ __align__(128) uint8_t g_V[RS * 16 * 56 * 512];
__device__ __align__(128) uint32_t g_P[RS * 16 * 14 * 32];
__device__ __align__(128) uint32_t g_U[RS * 16 * 56 * 32];
__device__ __align__(128) uint8_t g_ACC[98304];
__device__ unsigned g_FT[64 * 32];
__device__ unsigned g_CNT[NSEG * 32];
__device__ unsigned g_WD[32 * 32];
__device__ unsigned g_INIT, g_EXIT;
#define GT(k, i)

__host__ __device__ constexpr int sig0(int k) { return k == 6 ? 12 : 4 * (k >> 1) + (k & 1); }
__host__ __device__ constexpr int sig1(int k) { return k == 6 ? 13 : 4 * (k >> 1) + (k & 1) + 2; }
constexpr int SPIN = 1 << 22;

__device__ __forceinline__ uint32_t smem_u32(const void* p) { return (uint32_t)__cvta_generic_to_shared(p); }
__device__ __forceinline__ void mma16816(float* c, uint32_t a0, uint32_t a1, uint32_t a2, uint32_t a3, uint32_t b0, uint32_t b1) {
    asm volatile("mma.sync.aligned.m16n8k16.row.col.f32.bf16.bf16.f32 {%0,%1,%2,%3},{%4,%5,%6,%7},{%8,%9},{%0,%1,%2,%3};"
                 : "+f"(c[0]), "+f"(c[1]), "+f"(c[2]), "+f"(c[3]) : "r"(a0), "r"(a1), "r"(a2), "r"(a3), "r"(b0), "r"(b1));
}
__device__ __forceinline__ void mma16816z(float* c, uint32_t a0, uint32_t a1, uint32_t a2, uint32_t a3, uint32_t b0, uint32_t b1) {
    asm volatile("mma.sync.aligned.m16n8k16.row.col.f32.bf16.bf16.f32 {%0,%1,%2,%3},{%4,%5,%6,%7},{%8,%9},{%10,%10,%10,%10};"
                 : "=f"(c[0]), "=f"(c[1]), "=f"(c[2]), "=f"(c[3]) : "r"(a0), "r"(a1), "r"(a2), "r"(a3), "r"(b0), "r"(b1), "f"(0.f));
}
__device__ __forceinline__ void mma1688(float* c, uint32_t a0, uint32_t a1, uint32_t b0) {
    asm volatile("mma.sync.aligned.m16n8k8.row.col.f32.bf16.bf16.f32 {%0,%1,%2,%3},{%4,%5},{%6},{%0,%1,%2,%3};"
                 : "+f"(c[0]), "+f"(c[1]), "+f"(c[2]), "+f"(c[3]) : "r"(a0), "r"(a1), "r"(b0));
}
__device__ __forceinline__ void mmaq(float* c, const uint4& a, uint32_t b0, uint32_t b1) { mma16816(c, a.x, a.y, a.z, a.w, b0, b1); }
__device__ __forceinline__ void mmaqz(float* c, const uint4& a, uint32_t b0, uint32_t b1) { mma16816z(c, a.x, a.y, a.z, a.w, b0, b1); }
__device__ __forceinline__ uint32_t pack_bf16(float lo, float hi) {
    uint32_t r; asm("cvt.rn.bf16x2.f32 %0,%1,%2;" : "=r"(r) : "f"(hi), "f"(lo)); return r;
}
__device__ __forceinline__ uint32_t pack_bf16_again(float lo, float hi) {
    uint32_t r; asm("cvt.rn.relu.bf16x2.f32 %0,%1,%2;" : "=r"(r) : "f"(hi), "f"(lo)); return r;
}
__device__ __forceinline__ uint32_t pack_f16(float lo, float hi) {
    uint32_t r; asm("cvt.rn.f16x2.f32 %0,%1,%2;" : "=r"(r) : "f"(hi), "f"(lo)); return r;
}
__device__ __forceinline__ uint32_t prmt(uint32_t a, uint32_t b, uint32_t sel) { uint32_t r; asm("prmt.b32 %0,%1,%2,%3;" : "=r"(r) : "r"(a), "r"(b), "r"(sel)); return r; }
__device__ __forceinline__ uint32_t movm(uint32_t a) {
    uint32_t d; asm volatile("movmatrix.sync.aligned.m8n8.trans.b16 %0,%1;" : "=r"(d) : "r"(a)); return d;
}
__device__ __forceinline__ void ldsm4(uint32_t* r, uint32_t a) {
    asm volatile("ldmatrix.sync.aligned.m8n8.x4.shared.b16 {%0,%1,%2,%3},[%4];" : "=r"(r[0]), "=r"(r[1]), "=r"(r[2]), "=r"(r[3]) : "r"(a) : "memory");
}
__device__ __forceinline__ uint4 ldsm4q(uint32_t a) { uint32_t r[4]; ldsm4(r, a); return make_uint4(r[0], r[1], r[2], r[3]); }
__device__ __forceinline__ void stsm4(uint32_t a, const uint4& v) {
    asm volatile("stmatrix.sync.aligned.m8n8.x4.shared.b16 [%0],{%1,%2,%3,%4};" ::"r"(a), "r"(v.x), "r"(v.y), "r"(v.z), "r"(v.w) : "memory");
}
__device__ __forceinline__ void stsm4t(uint32_t a, const uint4& v) {
    asm volatile("stmatrix.sync.aligned.m8n8.x4.trans.shared.b16 [%0],{%1,%2,%3,%4};" ::"r"(a), "r"(v.x), "r"(v.y), "r"(v.z), "r"(v.w) : "memory");
}
__device__ __forceinline__ uint4 movm4(const uint4& v) { return make_uint4(movm(v.x), movm(v.y), movm(v.z), movm(v.w)); }
__device__ __forceinline__ void stsm2(uint32_t a, uint32_t x, uint32_t y) {
    asm volatile("stmatrix.sync.aligned.m8n8.x2.shared.b16 [%0],{%1,%2};" ::"r"(a), "r"(x), "r"(y) : "memory");
}
__device__ __forceinline__ uint4 lds128(uint32_t a) {
    uint4 v; asm volatile("ld.shared.v4.u32 {%0,%1,%2,%3},[%4];" : "=r"(v.x), "=r"(v.y), "=r"(v.z), "=r"(v.w) : "r"(a) : "memory"); return v;
}
__device__ __forceinline__ float4 lds128f(uint32_t a) {
    float4 v; asm volatile("ld.shared.v4.f32 {%0,%1,%2,%3},[%4];" : "=f"(v.x), "=f"(v.y), "=f"(v.z), "=f"(v.w) : "r"(a) : "memory"); return v;
}
__device__ __forceinline__ uint2 lds64(uint32_t a) {
    uint2 v; asm volatile("ld.shared.v2.u32 {%0,%1},[%2];" : "=r"(v.x), "=r"(v.y) : "r"(a) : "memory"); return v;
}
__device__ __forceinline__ float2 lds64f(uint32_t a) {
    float2 v; asm volatile("ld.shared.v2.f32 {%0,%1},[%2];" : "=f"(v.x), "=f"(v.y) : "r"(a) : "memory"); return v;
}
__device__ __forceinline__ uint32_t lds32(uint32_t a) {
    uint32_t v; asm volatile("ld.shared.u32 %0,[%1];" : "=r"(v) : "r"(a) : "memory"); return v;
}
__device__ __forceinline__ uint32_t lds32v(uint32_t a) {
    uint32_t v; asm volatile("ld.volatile.shared.u32 %0,[%1];" : "=r"(v) : "r"(a) : "memory"); return v;
}
__device__ __forceinline__ float lds32f(uint32_t a) { return __uint_as_float(lds32(a)); }
__device__ __forceinline__ void sts128(uint32_t a, uint32_t x, uint32_t y, uint32_t z, uint32_t w) {
    asm volatile("st.shared.v4.u32 [%0],{%1,%2,%3,%4};" ::"r"(a), "r"(x), "r"(y), "r"(z), "r"(w) : "memory");
}
__device__ __forceinline__ void sts64(uint32_t a, uint32_t x, uint32_t y) {
    asm volatile("st.shared.v2.u32 [%0],{%1,%2};" ::"r"(a), "r"(x), "r"(y) : "memory");
}
__device__ __forceinline__ void sts64f(uint32_t a, float x, float y) { sts64(a, __float_as_uint(x), __float_as_uint(y)); }
__device__ __forceinline__ void sts32(uint32_t a, uint32_t x) { asm volatile("st.shared.u32 [%0],%1;" ::"r"(a), "r"(x) : "memory"); }
__device__ __forceinline__ void sts32f(uint32_t a, float x) { sts32(a, __float_as_uint(x)); }
#define ADDR3(ins) "{.reg .u32 t; add.u32 t," ins "}"
template <int I> __device__ __forceinline__ uint4 lds128u(uint32_t a, uint32_t u) {
    uint4 v; asm volatile(ADDR3("%4,%5; ld.shared.v4.u32 {%0,%1,%2,%3},[t+%6];") : "=r"(v.x), "=r"(v.y), "=r"(v.z), "=r"(v.w) : "r"(a), "r"(u), "n"(I) : "memory"); return v;
}
template <int I> __device__ __forceinline__ float4 lds128fu(uint32_t a, uint32_t u) {
    const uint4 v = lds128u<I>(a, u); return make_float4(__uint_as_float(v.x), __uint_as_float(v.y), __uint_as_float(v.z), __uint_as_float(v.w));
}
template <int I> __device__ __forceinline__ uint2 lds64u(uint32_t a, uint32_t u) {
    uint2 v; asm volatile(ADDR3("%2,%3; ld.shared.v2.u32 {%0,%1},[t+%4];") : "=r"(v.x), "=r"(v.y) : "r"(a), "r"(u), "n"(I) : "memory"); return v;
}
template <int I> __device__ __forceinline__ float2 lds64fu(uint32_t a, uint32_t u) { const uint2 v = lds64u<I>(a, u); return make_float2(__uint_as_float(v.x), __uint_as_float(v.y)); }
template <int I> __device__ __forceinline__ uint4 ldsm4u(uint32_t a, uint32_t u) {
    uint4 v; asm volatile(ADDR3("%4,%5; ldmatrix.sync.aligned.m8n8.x4.shared.b16 {%0,%1,%2,%3},[t+%6];") : "=r"(v.x), "=r"(v.y), "=r"(v.z), "=r"(v.w) : "r"(a), "r"(u), "n"(I) : "memory"); return v;
}
template <int I> __device__ __forceinline__ uint4 ldsm4tu(uint32_t a, uint32_t u) {
    uint4 v; asm volatile(ADDR3("%4,%5; ldmatrix.sync.aligned.m8n8.x4.trans.shared.b16 {%0,%1,%2,%3},[t+%6];") : "=r"(v.x), "=r"(v.y), "=r"(v.z), "=r"(v.w) : "r"(a), "r"(u), "n"(I) : "memory"); return v;
}
__device__ __forceinline__ uint32_t uni(uint32_t v) { return __shfl_sync(0xffffffffu, v, 0); }
template <int I> __device__ __forceinline__ void sts128u(uint32_t a, uint32_t u, uint32_t x, uint32_t y, uint32_t z, uint32_t w) {
    asm volatile(ADDR3("%0,%1; st.shared.v4.u32 [t+%2],{%3,%4,%5,%6};") ::"r"(a), "r"(u), "n"(I), "r"(x), "r"(y), "r"(z), "r"(w) : "memory");
}
template <int I> __device__ __forceinline__ void sts64u(uint32_t a, uint32_t u, uint32_t x, uint32_t y) {
    asm volatile(ADDR3("%0,%1; st.shared.v2.u32 [t+%2],{%3,%4};") ::"r"(a), "r"(u), "n"(I), "r"(x), "r"(y) : "memory");
}
__device__ __forceinline__ uint32_t add_here(uint32_t a, uint32_t b) { uint32_t r; asm volatile("add.u32 %0,%1,%2;" : "=r"(r) : "r"(a), "r"(b)); return r; }
__device__ __forceinline__ uint8_t* add_here(uint8_t* p, uint32_t o) { uint8_t* r; asm volatile("{.reg .u64 t; cvt.u64.u32 t,%2; add.u64 %0,%1,t;}" : "=l"(r) : "l"(p), "r"(o)); return r; }
__device__ __forceinline__ uint32_t mapa(uint32_t a, uint32_t r) {
    uint32_t o; asm("mapa.shared::cluster.u32 %0,%1,%2;" : "=r"(o) : "r"(a), "r"(r)); return o;
}
__device__ __forceinline__ void st_async4(uint32_t dst, uint32_t bar, float x, float y, float z, float w) {
    asm volatile("st.async.weak.shared::cluster.mbarrier::complete_tx::bytes.v4.f32 [%0],{%1,%2,%3,%4},[%5];"
                 ::"r"(dst), "f"(x), "f"(y), "f"(z), "f"(w), "r"(bar) : "memory");
}
__device__ __forceinline__ void st_async2(uint32_t dst, uint32_t bar, float x, float y) {
    asm volatile("st.async.weak.shared::cluster.mbarrier::complete_tx::bytes.v2.f32 [%0],{%1,%2},[%3];"
                 ::"r"(dst), "f"(x), "f"(y), "r"(bar) : "memory");
}
__device__ __forceinline__ void st_async1(uint32_t dst, uint32_t bar, uint32_t x) {
    asm volatile("st.async.weak.shared::cluster.mbarrier::complete_tx::bytes.u32 [%0],%1,[%2];" ::"r"(dst), "r"(x), "r"(bar) : "memory");
}
__device__ __forceinline__ float ldr32f(uint32_t a) {
    float v; asm volatile("ld.shared::cluster.f32 %0,[%1];" : "=f"(v) : "r"(a) : "memory"); return v;
}
__device__ __forceinline__ void mbar_init(uint32_t bar, int cnt) { asm volatile("mbarrier.init.shared::cta.b64 [%0],%1;" ::"r"(bar), "r"(cnt) : "memory"); }
__device__ __forceinline__ void mbar_expect(uint32_t bar, int bytes) {
    asm volatile("mbarrier.arrive.expect_tx.shared::cta.b64 _,[%0],%1;" ::"r"(bar), "r"(bytes) : "memory");
}
__device__ __forceinline__ void mbar_arrive(uint32_t a) { asm volatile("mbarrier.arrive.release.cta.shared::cta.b64 _,[%0];" ::"r"(a) : "memory"); }
__device__ __forceinline__ void mbar_wait(uint32_t bar, uint32_t parity) {
    uint32_t ok; int it = 0;
    while (true) {
        asm volatile("{.reg .pred p; mbarrier.try_wait.parity.shared::cta.b64 p,[%1],%2; selp.u32 %0,1,0,p;}" : "=r"(ok) : "r"(bar), "r"(parity) : "memory");
        if (ok) break;
        if (++it > SPIN) __trap();
    }
}
__device__ __forceinline__ void mbar_wait_cl(uint32_t bar) {
    uint32_t ok; int it = 0;
    while (true) {
        asm volatile("{.reg .pred p; mbarrier.try_wait.parity.relaxed.cluster.shared::cta.b64 p,[%1],0; selp.u32 %0,1,0,p;}" : "=r"(ok) : "r"(bar) : "memory");
        if (ok) break;
        if (++it > SPIN) __trap();
    }
    asm volatile("fence.acquire.sync_restrict::shared::cluster.cluster;" ::: "memory");
}
__device__ __forceinline__ void bulk_g2s(uint32_t dst, const void* src, int bytes, uint32_t bar) {
    asm volatile("cp.async.bulk.shared::cluster.global.mbarrier::complete_tx::bytes [%0],[%1],%2,[%3];"
                 ::"r"(dst), "l"(src), "r"(bytes), "r"(bar) : "memory");
}
__device__ __forceinline__ void tma2d(uint32_t dst, const CUtensorMap* map, int x, int y, uint32_t bar) {
    asm volatile("cp.async.bulk.tensor.2d.shared::cluster.global.mbarrier::complete_tx::bytes [%0],[%1,{%2,%3}],[%4];"
                 ::"r"(dst), "l"(map), "r"(x), "r"(y), "r"(bar) : "memory");
}
__device__ __forceinline__ void tma2d_pair(uint32_t dst, const CUtensorMap* map, int x, int y, uint32_t bar) {
    asm volatile("cp.async.bulk.tensor.2d.shared::cluster.global.mbarrier::complete_tx::bytes.multicast::cluster [%0],[%1,{%2,%3}],[%4],%5;"
                 ::"r"(dst), "l"(map), "r"(x), "r"(y), "r"(bar), "h"((uint16_t)3) : "memory");
}
__device__ __forceinline__ void tma3d(uint32_t dst, const CUtensorMap* map, int x, int y, int z, uint32_t bar) {
    asm volatile("cp.async.bulk.tensor.3d.shared::cluster.global.mbarrier::complete_tx::bytes [%0],[%1,{%2,%3,%4}],[%5];"
                 ::"r"(dst), "l"(map), "r"(x), "r"(y), "r"(z), "r"(bar) : "memory");
}
__device__ __forceinline__ void prefetch_l2(const void* p, int bytes) {
    asm volatile("cp.async.bulk.prefetch.L2.global [%0],%1;" ::"l"(p), "r"(bytes) : "memory");
}
__device__ __forceinline__ int fresh_lane() { int l; asm volatile("mov.u32 %0,%%laneid;" : "=r"(l)); return __shfl_sync(0xffffffffu, l, l); }
__device__ __forceinline__ bool elect_one() {
    uint32_t r; asm volatile("{.reg .pred p; elect.sync _|p,0xffffffff; selp.u32 %0,1,0,p;}" : "=r"(r)); return r;
}
__device__ __forceinline__ void bar_sync(int id, int n) { asm volatile("bar.sync %0,%1;" ::"r"(id), "r"(n) : "memory"); }
__device__ __forceinline__ void bar_arrive(int id, int n) { asm volatile("bar.arrive %0,%1;" ::"r"(id), "r"(n) : "memory"); }
__device__ __forceinline__ uint4 ld_relaxed4(const void* p) {
    uint4 v; asm volatile("ld.relaxed.gpu.global.v4.u32 {%0,%1,%2,%3},[%4];" : "=r"(v.x), "=r"(v.y), "=r"(v.z), "=r"(v.w) : "l"(p) : "memory"); return v;
}
__device__ __forceinline__ unsigned ld_relaxed(const unsigned* p) {
    unsigned v; asm volatile("ld.relaxed.gpu.global.u32 %0,[%1];" : "=r"(v) : "l"(p) : "memory"); return v;
}
__device__ __forceinline__ void st_relaxed(unsigned* p, unsigned v) { asm volatile("st.relaxed.gpu.global.u32 [%0],%1;" ::"l"(p), "r"(v) : "memory"); }
__device__ __forceinline__ void stg32(void* p, uint32_t v) { asm volatile("st.global.u32 [%0],%1;" ::"l"(p), "r"(v) : "memory"); }
__device__ __forceinline__ void red_inc(unsigned* p) { asm volatile("red.relaxed.gpu.global.add.u32 [%0],1;" ::"l"(p) : "memory"); }
__device__ __forceinline__ void fence_gpu() { asm volatile("fence.acq_rel.gpu;" ::: "memory"); }
__device__ __forceinline__ void wait_count(const unsigned* p, unsigned goal, unsigned sleep_ns) {
    int it = 0;
    while ((int)(ld_relaxed(p) - goal) < 0) { if (sleep_ns) __nanosleep(sleep_ns); if (++it > SPIN) __trap(); }
}
__device__ __forceinline__ void wait_count_warp(const unsigned* p, unsigned goal, unsigned sleep_ns) {
    int it = 0;
    while (__any_sync(0xffffffffu, (int)(ld_relaxed(p) - goal) < 0)) { if (sleep_ns) __nanosleep(sleep_ns); if (++it > SPIN) __trap(); }
}
__device__ __forceinline__ void red_bf16x8(void* p, uint32_t x, uint32_t y, uint32_t z, uint32_t w) {
    asm volatile("red.relaxed.gpu.global.add.noftz.v4.bf16x2 [%0],{%1,%2,%3,%4};" ::"l"(p), "r"(x), "r"(y), "r"(z), "r"(w) : "memory");
}
__device__ __forceinline__ void mbar_arrive_if(bool on, uint32_t a) {
    asm volatile("{.reg .pred p; setp.ne.b32 p,%1,0; @p mbarrier.arrive.release.cta.shared::cta.b64 _,[%0];}" ::"r"(a), "r"((int)on) : "memory");
}
__device__ __forceinline__ void mbar_arrive_cl_if(bool on, uint32_t a) {
    asm volatile("{.reg .pred p; setp.ne.b32 p,%1,0; @p mbarrier.arrive.relaxed.cluster.shared::cluster.b64 _,[%0];}" ::"r"(a), "r"((int)on) : "memory");
}
__device__ __forceinline__ uint32_t any_reg() { uint32_t r; asm volatile("" : "=r"(r)); return r; }
__device__ __forceinline__ float ex2(float x) { float y; asm("ex2.approx.ftz.f32 %0,%1;" : "=f"(y) : "f"(x)); return y; }
__device__ __forceinline__ float rcp(float x) { float y; asm("rcp.approx.ftz.f32 %0,%1;" : "=f"(y) : "f"(x)); return y; }
__device__ __forceinline__ uint32_t clk() {
    uint32_t c; asm volatile("{.reg .u64 t; .reg .u32 h; mov.u64 t,%%clock64; mov.b64 {%0,h},t;}" : "=r"(c)::"memory"); return c;
}
__device__ __forceinline__ uint32_t hadd_bf(uint32_t a, uint32_t b) { uint32_t r; asm("add.rn.bf16x2 %0,%1,%2;" : "=r"(r) : "r"(a), "r"(b)); return r; }
__device__ __forceinline__ uint32_t hmul_bf(uint32_t a, uint32_t b) { uint32_t r; asm("mul.rn.bf16x2 %0,%1,%2;" : "=r"(r) : "r"(a), "r"(b)); return r; }
__device__ __forceinline__ uint32_t hsum4(uint32_t a, uint32_t b, uint32_t c, uint32_t d) { return hadd_bf(hadd_bf(a, b), hadd_bf(c, d)); }
__device__ __forceinline__ uint32_t amax_bf(uint32_t a, uint32_t b) { uint32_t r; asm("max.xorsign.abs.bf16x2 %0,%1,%2;" : "=r"(r) : "r"(a), "r"(b)); return r; }
__device__ __forceinline__ float4 sum4(float4 a, float4 b, float4 c, float4 d) {
    return make_float4((a.x + b.x) + (c.x + d.x), (a.y + b.y) + (c.y + d.y), (a.z + b.z) + (c.z + d.z), (a.w + b.w) + (c.w + d.w));
}
__device__ __forceinline__ void cluster_sync() { asm volatile("barrier.cluster.arrive.release.aligned; barrier.cluster.wait.acquire.aligned;" ::: "memory"); }
#define SCHED_FENCE(z, k) do { if ((z) == (k)) __trap(); } while (0)

template <int TB>
__device__ __forceinline__ void wgmma224(float* d, uint64_t da, uint64_t db, int accumulate) {
    asm volatile("{.reg .pred p; setp.ne.b32 p,%114,0;\n"
                 "wgmma.mma_async.sync.aligned.m64n224k16.f32.bf16.bf16 {%0,%1,%2,%3,%4,%5,%6,%7,%8,%9,%10,%11,%12,%13,%14,%15,%16,%17,%18,%19,%20,%21,%22,%23,%24,%25,%26,%27,%28,%29,%30,%31,%32,%33,%34,%35,%36,%37,%38,%39,%40,%41,%42,%43,%44,%45,%46,%47,%48,%49,%50,%51,%52,%53,%54,%55,%56,%57,%58,%59,%60,%61,%62,%63,%64,%65,%66,%67,%68,%69,%70,%71,%72,%73,%74,%75,%76,%77,%78,%79,%80,%81,%82,%83,%84,%85,%86,%87,%88,%89,%90,%91,%92,%93,%94,%95,%96,%97,%98,%99,%100,%101,%102,%103,%104,%105,%106,%107,%108,%109,%110,%111},%112,%113,p,1,1,0,%115;}"
                 : "+f"(d[0]), "+f"(d[1]), "+f"(d[2]), "+f"(d[3]), "+f"(d[4]), "+f"(d[5]), "+f"(d[6]), "+f"(d[7]), "+f"(d[8]), "+f"(d[9]), "+f"(d[10]), "+f"(d[11]), "+f"(d[12]), "+f"(d[13]), "+f"(d[14]), "+f"(d[15]), "+f"(d[16]), "+f"(d[17]), "+f"(d[18]), "+f"(d[19]), "+f"(d[20]), "+f"(d[21]), "+f"(d[22]), "+f"(d[23]), "+f"(d[24]), "+f"(d[25]), "+f"(d[26]), "+f"(d[27]), "+f"(d[28]), "+f"(d[29]), "+f"(d[30]), "+f"(d[31]), "+f"(d[32]), "+f"(d[33]), "+f"(d[34]), "+f"(d[35]), "+f"(d[36]), "+f"(d[37]), "+f"(d[38]), "+f"(d[39]), "+f"(d[40]), "+f"(d[41]), "+f"(d[42]), "+f"(d[43]), "+f"(d[44]), "+f"(d[45]), "+f"(d[46]), "+f"(d[47]), "+f"(d[48]), "+f"(d[49]), "+f"(d[50]), "+f"(d[51]), "+f"(d[52]), "+f"(d[53]), "+f"(d[54]), "+f"(d[55]), "+f"(d[56]), "+f"(d[57]), "+f"(d[58]), "+f"(d[59]), "+f"(d[60]), "+f"(d[61]), "+f"(d[62]), "+f"(d[63]), "+f"(d[64]), "+f"(d[65]), "+f"(d[66]), "+f"(d[67]), "+f"(d[68]), "+f"(d[69]), "+f"(d[70]), "+f"(d[71]), "+f"(d[72]), "+f"(d[73]), "+f"(d[74]), "+f"(d[75]), "+f"(d[76]), "+f"(d[77]), "+f"(d[78]), "+f"(d[79]), "+f"(d[80]), "+f"(d[81]), "+f"(d[82]), "+f"(d[83]), "+f"(d[84]), "+f"(d[85]), "+f"(d[86]), "+f"(d[87]), "+f"(d[88]), "+f"(d[89]), "+f"(d[90]), "+f"(d[91]), "+f"(d[92]), "+f"(d[93]), "+f"(d[94]), "+f"(d[95]), "+f"(d[96]), "+f"(d[97]), "+f"(d[98]), "+f"(d[99]), "+f"(d[100]), "+f"(d[101]), "+f"(d[102]), "+f"(d[103]), "+f"(d[104]), "+f"(d[105]), "+f"(d[106]), "+f"(d[107]), "+f"(d[108]), "+f"(d[109]), "+f"(d[110]), "+f"(d[111])
                 : "l"(da), "l"(db), "r"(accumulate), "n"(TB));
}
__device__ __forceinline__ uint64_t sdesc(uint32_t addr, uint32_t lbo, uint32_t sbo, uint64_t swizzle) {
    return (uint64_t)((addr & 0x3FFFF) >> 4) | ((uint64_t)(lbo >> 4) << 16) | ((uint64_t)(sbo >> 4) << 32) | (swizzle << 62);
}
__device__ __forceinline__ void wg_fence() { asm volatile("wgmma.fence.sync.aligned;" ::: "memory"); }
__device__ __forceinline__ void wg_commit() { asm volatile("wgmma.commit_group.sync.aligned;" ::: "memory"); }
template <int N> __device__ __forceinline__ void wg_wait() { asm volatile("wgmma.wait_group.sync.aligned %0;" ::"n"(N) : "memory"); }
constexpr float LOG2E = 1.4426950408889634f;
constexpr uint32_t ONE2 = 0x3f803f80u;
constexpr uint32_t CNT16 = 0x41800000u;
constexpr uint32_t SAFE_LO = (127u - 40u) << 23, SAFE_SPAN = 80u << 23;

constexpr int C_IO = 0;
constexpr int C_UP = 2176, C_UW = 2 * C_UP + 16;
constexpr int C_U = C_IO + 32768;
constexpr int C_RN = 16, C_RX = 576, C_RM = 624, C_RF = C_RM + 4 * 64, C_RW = C_RF + 2 * 80;
constexpr int C_R = C_U + 8 * C_UW;
constexpr int C_TW = 56 * 144;
constexpr int C_T = C_R + 8 * C_RW * 4;
constexpr int C_END = C_T + 8 * C_TW;

struct SsmArgs { const __nv_bfloat16 *lar, *aim, *cre, *cim, *ldt, *dsk; };
struct cpx { float r, i; };
__device__ __forceinline__ cpx csq(cpx a) { return {fmaf(a.r, a.r, -a.i * a.i), (a.r + a.r) * a.i}; }
__device__ __forceinline__ cpx cexp(float er, float wi, float p) { const float e = ex2(er * p), x = wi * p; return {e * __cosf(x), e * __sinf(x)}; }
struct hfac { uint32_t v, s; };
__device__ __forceinline__ hfac hfactor(cpx a) { return {pack_f16(a.r, a.i), pack_f16(-a.i, a.r)}; }
__device__ __forceinline__ uint32_t hcmul(uint32_t a, hfac b) {
    uint32_t r;
    asm("{.reg .f16 l,h; .reg .b32 x,y; mov.b32 {l,h},%1; mov.b32 x,{l,l}; mov.b32 y,{h,h}; mul.rn.f16x2 x,x,%2; fma.rn.f16x2 %0,y,%3,x;}" : "=r"(r) : "r"(a), "r"(b.v), "r"(b.s));
    return r;
}
__device__ __forceinline__ void mmah(float* c, const uint4& a, uint32_t b0, uint32_t b1) {
    asm volatile("mma.sync.aligned.m16n8k16.row.col.f32.f16.f16.f32 {%0,%1,%2,%3},{%4,%5,%6,%7},{%8,%9},{%0,%1,%2,%3};"
                 : "+f"(c[0]), "+f"(c[1]), "+f"(c[2]), "+f"(c[3]) : "r"(a.x), "r"(a.y), "r"(a.z), "r"(a.w), "r"(b0), "r"(b1));
}

__device__ __forceinline__ void ssm_kernel_values(uint32_t tb, uint32_t rb, int d, int lane, const SsmArgs& p) {
    const int g = lane >> 2, t = lane & 3;
    const float dt = __bfloat162float(__float2bfloat16(expf(__bfloat162float(p.ldt[d]))));
    float up;
    {
        const uint4 a = __ldg((const uint4*)(p.lar + d * NST) + lane), b = __ldg((const uint4*)(p.aim + d * NST) + lane);
        const uint4 v = __ldg((const uint4*)(p.cre + d * NST) + lane), z = __ldg((const uint4*)(p.cim + d * NST) + lane);
        sts128(rb + lane * 16, a.x, a.y, a.z, a.w); sts128(rb + 512 + lane * 16, b.x, b.y, b.z, b.w);
        sts128(rb + 1024 + lane * 16, v.x, v.y, v.z, v.w); sts128(rb + 1536 + lane * 16, z.x, z.y, z.z, z.w);
        const uint32_t m = amax_bf(amax_bf(amax_bf(v.x, v.y), amax_bf(v.z, v.w)), amax_bf(amax_bf(z.x, z.y), amax_bf(z.z, z.w)));
        const int e = __reduce_max_sync(0xffffffffu, max(m & 0x7f800000u, (m << 16) & 0x7f800000u)) >> 23;
        up = __uint_as_float((uint32_t)min(267 - e, 253) << 23);
    }
    float acc[2][3][4];
#pragma unroll
    for (int i = 0; i < 24; i++) (&acc[0][0][0])[i] = 0.f;
    const uint32_t wa = tb + lane * 4;
    const uint32_t la_ = tb + (lane & 15) * 144 + (lane >> 4) * 16, lb_ = tb + (32 + (lane & 7)) * 144 + (lane >> 3) * 16;
    sts32(wa, 0x00003c00u); sts32(wa + 53 * 144, 0u); sts32(wa + 54 * 144, 0u); sts32(wa + 55 * 144, 0u);
    auto par = [&](int o) { uint32_t k; asm volatile("{.reg .u16 h; ld.shared.u16 h,[%1]; cvt.u32.u16 %0,h;}" : "=r"(k) : "r"(rb + lane * 2 + o) : "memory"); return k; };
    __syncwarp();
    uint32_t la = par(0), ai = par(512), cr = par(1024), ci = par(1536);
#pragma unroll 1
    for (int it = 1; it <= 8; it++) {
        __syncwarp();
        const float er = (-__bfloat162float(__float2bfloat16(expf(__uint_as_float(la << 16)))) * dt) * LOG2E;
        const float wi = __uint_as_float(ai << 16) * dt;
        uint32_t x[21], y[32];
        x[0] = pack_f16(__uint_as_float(cr << 16) * up, __uint_as_float(ci << 16) * -up);
        la = par(64 * it); ai = par(512 + 64 * it); cr = par(1024 + 64 * it); ci = par(1536 + 64 * it);
        const cpx c1 = cexp(er, wi, 1.f), w8 = cexp(er, wi, 8.f), w64 = cexp(er, wi, 64.f), c256 = cexp(er, wi, 256.f);
        const cpx w1 = {c1.r, -c1.i}, w2 = csq(w1), w16 = csq(w8), w256 = {c256.r, -c256.i}, w512 = csq(w256);
        const hfac h1 = hfactor(w1), h2 = hfactor(w2), h4 = hfactor(csq(w2)), h256 = hfactor(w256), h512 = hfactor(w512), h1024 = hfactor(csq(w512));
        const hfac f[4] = {hfactor(w16), hfactor(csq(w16)), hfactor(w64), hfactor(csq(w64))};
        x[1] = hcmul(x[0], h1); x[2] = hcmul(x[0], h2); x[3] = hcmul(x[1], h2);
#pragma unroll
        for (int k = 0; k < 4; k++) x[4 + k] = hcmul(x[k], h4);
#pragma unroll
        for (int k = 0; k < 4; k++) x[8 + k] = hcmul(x[2 * k], h256);
        x[12] = hcmul(x[0], h512); x[13] = hcmul(x[4], h512); x[14] = hcmul(x[8], h512); x[15] = hcmul(x[10], h512);
        x[16] = hcmul(x[0], h1024); x[17] = hcmul(x[8], h1024); x[18] = hcmul(x[12], h1024); x[19] = hcmul(x[14], h1024); x[20] = hcmul(x[16], h1024);
        y[0] = 0; y[1] = pack_f16(w8.r, w8.i);
#pragma unroll
        for (int k = 2; k < 32; k++) {
            const int l = k < 4 ? 0 : (k < 8 ? 1 : (k < 16 ? 2 : 3));
            y[k] = k == (2 << l) ? f[l].v : hcmul(y[k - (2 << l)], f[l]);
        }
#pragma unroll
        for (int k = 0; k < 21; k++) sts32(wa + (32 + k) * 144, x[k]);
#pragma unroll
        for (int k = 1; k < 32; k++) sts32(wa + k * 144, y[k]);
        __syncwarp();
#pragma unroll
        for (int kp = 0; kp < 2; kp++) {
            const uint4 b0 = ldsm4q(lb_ + kp * 64), b1 = ldsm4q(lb_ + 8 * 144 + kp * 64), b2 = ldsm4q(lb_ + 16 * 144 + kp * 64);
#pragma unroll
            for (int m = 0; m < 2; m++) {
                const uint4 a0 = ldsm4q(la_ + m * 16 * 144 + kp * 64), a1 = ldsm4q(la_ + m * 16 * 144 + kp * 64 + 32);
                mmah(acc[m][0], a0, b0.x, b0.y); mmah(acc[m][1], a0, b1.x, b1.y); mmah(acc[m][2], a0, b2.x, b2.y);
                mmah(acc[m][0], a1, b0.z, b0.w); mmah(acc[m][1], a1, b1.z, b1.w); mmah(acc[m][2], a1, b2.z, b2.w);
            }
        }
    }
    __syncwarp();
    const float down = __uint_as_float((254u << 23) - __float_as_uint(up)), dt2 = 2.f * dt;
    auto put16 = [&](int pos, float v) { asm volatile("st.shared.u16 [%0],%1;" ::"r"(tb + pos * 2), "h"(__bfloat16_as_ushort(__float2bfloat16(v * dt2 * down))) : "memory"); };
    auto get16 = [&](int pos) { uint32_t k; asm volatile("{.reg .u16 h; ld.shared.u16 h,[%1]; cvt.u32.u16 %0,h;}" : "=r"(k) : "r"(tb + pos * 2) : "memory"); return k; };
    const int o1 = t < 2 ? 256 + 4 * t : 256 * t, s1 = t < 2 ? 2 : 4;
#pragma unroll
    for (int m = 0; m < 2; m++)
#pragma unroll
        for (int e = 0; e < 4; e++) {
            const int b = 128 * m + 8 * g + 64 * (e >> 1);
            put16(b + 2 * t + (e & 1), acc[m][0][e]); put16(b + o1 + s1 * (e & 1), acc[m][1][e]);
            put16(b + 1024 + 512 * t + 256 * (e & 1), acc[m][2][e]);
        }
    __syncwarp();
    constexpr int NIL = 3064;
    uint32_t r[31];
    auto pos = [&](int j, int o) {
        const int y = lane + 32 * j - C_RN - o, z = lane - o, rz = (z + ((z >> 1) & 1)) & ~1;
        if (j == 0) return y < 0 ? NIL : y;
        if (j < 8) return y;
        if (j == 8) return y < 256 ? y : rz + 32 * j - C_RN;
        if (j < 16) return rz + 32 * j - C_RN;
        return y < 512 ? rz + 32 * j - C_RN : (y <= 514 ? 512 : NIL);
    };
#pragma unroll
    for (int j = 0; j < 17; j++) r[j] = get16(pos(j, 0)) | (get16(pos(j, 1)) << 16);
    const uint32_t k1024 = get16(1024);
    r[17] = (lane == 19 || lane == 20 ? k1024 : 0u) | (lane == 20 || lane == 21 ? k1024 << 16 : 0u);
#pragma unroll
    for (int j = 0; j < 8; j++) {
        const int q = lane + 32 * (j & 1) + 16, o = 4 * (j >> 1) + 4;
        r[18 + j] = get16(q >= 32 && q < 64 ? 16 * q + o : NIL) | (get16(q >= 33 && q < 65 ? 16 * q - 16 + o : NIL) << 16);
    }
#pragma unroll
    for (int j = 0; j < 5; j++) {
        const int i = lane + 32 * j, hi = i >= 80, q = i - 80 * hi + 48, o = 8 * hi + 8;
        r[26 + j] = get16(q >= 64 ? 16 * q + o : NIL) | (get16(q >= 65 ? 16 * q - 16 + o : NIL) << 16);
    }
    const uint32_t ro = rb + lane * 4;
#pragma unroll
    for (int j = 0; j < 17; j++) sts32(ro + j * 128, r[j]);
    sts32(ro + 17 * 128, 0u); sts32(ro + C_RX * 4, r[17]); sts32(rb + (C_RX + 32 + (lane & 15)) * 4, 0u);
#pragma unroll
    for (int j = 0; j < 13; j++) sts32(ro + C_RM * 4 + j * 128, r[18 + j]);
}

template <int E0, int NE, int NK>
__device__ __forceinline__ void ssm_grouped(float (&acc)[16][4], uint32_t ub, uint32_t ta, int off, int width, int lane, uint32_t zero) {
    const int g = lane >> 2, t = lane & 3, mi = lane >> 3;
    const bool sh = off >= 8;
    const uint32_t ua = ub + ((mi ^ sh) & 1) * C_UP + (8 + (lane & 7) + ((mi + sh) >> 1) - 1 - sh) * 16;
    uint32_t band[5];
#pragma unroll
    for (int i = 0; i < 5; i++) {
        const int z = g - 2 * t + 8 - 8 * i + (sh ? 24 : 16) - off;
        band[i] = ((unsigned)z < (unsigned)width ? 0x3f80u : 0u) | ((unsigned)(z - 1) < (unsigned)width ? 0x3f800000u : 0u);
    }
    const uint4 q0 = make_uint4(band[1], band[0], band[2], band[1] ^ zero), q1 = make_uint4(band[3], band[2] ^ zero, band[4], band[3] ^ zero);
    uint32_t tp[NE][2];
#pragma unroll
    for (int e = 0; e < NE; e++) { tp[e][0] = lds32(ta + (8 * e + 16) * 4); tp[e][1] = lds32v(ta + (8 * e + 8) * 4); }
#pragma unroll
    for (int k = 0; k < NK; k++) {
        float w0[4], w1[4];
        const uint4 u0 = ldsm4q(ua + k * 256), u1 = ldsm4q(ua + k * 256 + 128);
        mmaqz(w0, q0, u0.x, u0.y); mmaqz(w1, q0, u1.x, u1.y);
        mmaq(w0, q1, u0.z, u0.w); mmaq(w1, q1, u1.z, u1.w);
        const uint4 a = make_uint4(pack_bf16(w0[0], w0[1]), pack_bf16(w0[2], w0[3]), pack_bf16(w1[0], w1[1]), pack_bf16(w1[2], w1[3]));
#pragma unroll
        for (int e = 0; e < NE; e++) if (2 * k + E0 + e < 16) mmaq(acc[2 * k + E0 + e], a, tp[e][0], tp[e][1]);
    }
}

__device__ __forceinline__ void ssm_unit(uint32_t sb, uint32_t bar, uint32_t par, bool init, int d0, const SsmArgs& p, const CUtensorMap* mapU, int barid, uint32_t zero) {
    const int lane = fresh_lane(), ch = __shfl_sync(0xffffffffu, threadIdx.x >> 5, 0);
    const int g = lane >> 2, t = lane & 3, mi = lane >> 3;
    if (ch == 0 && elect_one()) {
        if (init) { mbar_init(bar, 1); asm volatile("fence.proxy.async.shared::cta;" ::: "memory"); }
        mbar_expect(bar, 32768);
#pragma unroll 1
        for (int i = 0; i < 8; i++) tma2d(sb + C_IO + i * 4096, mapU, d0, 256 * i, bar);
    }
    const uint32_t ub = sb + C_U + ch * C_UW, rb = sb + C_R + ch * C_RW * 4;
    if (lane < 16) sts128(ub + (lane >> 3) * C_UP + (lane & 7) * 16, 0u, 0u, 0u, 0u);
    const uint32_t dk = __bfloat16_as_ushort(p.dsk[d0 + ch]);
    ssm_kernel_values(sb + C_T + ch * C_TW, rb, d0 + ch, lane, p);
    if (ch == 0 && lane == 0) GT(0, 8);
    const uint32_t ioa = sb + C_IO + ch * 4096 + lane * 16, pla = sb + C_U + (lane & 7) * C_UW + (mi & 1) * C_UP + (8 + 16 * ch + (mi >> 1)) * 16;
    if (init) bar_sync(barid, 256);
    mbar_wait(bar, par);
#pragma unroll
    for (int i = 0; i < 8; i++) stsm4t(pla + i * 32, ldsm4q(ioa + i * 512));
    bar_sync(barid, 256);
    float acc[16][4];
    const uint32_t ua = ub + (mi & 1) * C_UP + (8 + 8 * (mi >> 1) + (lane & 7)) * 16, ra = rb + (C_RN + g - 2 * t) * 4;
    {
        const uint32_t dg = (g == 2 * t ? dk : 0u) | (g == 2 * t + 1 ? dk << 16 : 0u);
        const uint4 q = make_uint4(dg, dg & zero, dk & zero, dg ^ zero);
#pragma unroll
        for (int j = 0; j < 8; j++) { const uint4 b = ldsm4q(ua + j * 256); mmaqz(acc[2 * j], q, b.x, b.y); mmaqz(acc[2 * j + 1], q, b.z, b.w); }
    }
#pragma unroll 1
    for (int rho = 0; rho < 8; rho++) {
        uint32_t b[16][2];
#pragma unroll
        for (int j = 0; j < 8; j++) { const uint4 v = ldsm4q(ua + j * 256 - rho * 16); b[2 * j][0] = v.x; b[2 * j][1] = v.y; b[2 * j + 1][0] = v.z; b[2 * j + 1][1] = v.w; }
        auto diag = [&](uint32_t a, int i) {
            const uint4 q = make_uint4(lds32(a), lds32(a + 32), lds32(a - 32), lds32v(a));
#pragma unroll
            for (int j = i; j < 16; j++) mmaq(acc[j], q, b[j - i][0], b[j - i][1]);
        };
#pragma unroll
        for (int i = 0; i < 4; i++) diag(ra + rho * 64 + i * 512, i);
        if (rho < 2) { diag(ra + rho * 64 + 2048, 4); diag(ra + rho * 64 + C_RX * 4, 8); }
    }
    const uint32_t ta = rb + (g - 2 * t) * 4;
#pragma unroll 1
    for (int ph = 0; ph < 4; ph++) ssm_grouped<4, 6, 6>(acc, ub, ta + (C_RM + 64 * ph) * 4, 4 * ph + 3 - (ph & 1), 3 + 2 * (ph & 1), lane, zero);
#pragma unroll 1
    for (int ph = 0; ph < 2; ph++) ssm_grouped<8, 8, 4>(acc, ub, ta + (C_RF + 80 * ph) * 4, 5 + 7 * ph, 7 + 2 * ph, lane, zero);
    if (ch == 0 && lane == 0) GT(0, 9);
    __syncwarp();
#pragma unroll
    for (int j = 0; j < 8; j++)
        stsm4t(ua + j * 256, make_uint4(pack_bf16(acc[2 * j][0], acc[2 * j][1]), pack_bf16(acc[2 * j][2], acc[2 * j][3]),
                                        pack_bf16(acc[2 * j + 1][0], acc[2 * j + 1][1]), pack_bf16(acc[2 * j + 1][2], acc[2 * j + 1][3])));
    bar_sync(barid, 256);
#pragma unroll
    for (int i = 0; i < 8; i++) stsm4t(ioa + i * 512, ldsm4q(pla + i * 32));
    asm volatile("fence.proxy.async.shared::cta;" ::: "memory");
}
__device__ __forceinline__ void ssm_store(uint32_t sb, int d0, int i, const CUtensorMap* mapY) {
    asm volatile("cp.async.bulk.tensor.2d.global.shared::cta.bulk_group [%0,{%1,%2}],[%3];" ::"l"(mapY), "r"(d0), "r"(128 * i), "r"(sb + C_IO + i * 2048) : "memory");
    asm volatile("cp.async.bulk.commit_group;" ::: "memory");
}

#define TRIG_DELAY 0
#define UW0 7
#define PF2 0
#define CLUSTER 4
#define TW0 1
#define GO_DEP 8
#define POLL_DELAY 400
constexpr int S_V = 0, S_KO = 7168, S_KS = 14336, S_X = 21504, S_ONE = 29184, STGB = 29696;
constexpr int R_STG = C_U;
constexpr int R_WB = R_STG + 3 * STGB, WB = 8192;
constexpr int W_W0 = 0;
constexpr int W_MB = 3584, W_TB = 5632, W_SMI = 7680;
constexpr int W_UP = 3584, W_QRT = 5632;
constexpr int W_TAB = 4 * WB + 6144;
constexpr int R_SMM = R_WB + 8 * WB;
constexpr int R_LS = R_SMM + 4096;
constexpr int R_ALIAS_END = R_LS + 10240;
constexpr int R_MISC = (R_ALIAS_END > C_END ? R_ALIAS_END : C_END);
constexpr int R_BAR = R_MISC + 16;
constexpr int B_KV = 0, B_SM = 512, B_LS = 1024, B_H = 1536, B_PUB = 2048, B_Z = 2560;
constexpr int R_SMEM = R_BAR + 3072;
static_assert(R_SMEM <= 232448, "smem");
enum { BR_MB = 1, BR_SM = 2, BR_UP = 3, BR_RED = 4, BR_PRO = 5, BR_ALL = 6, BR_H = 7, BR_POLL = 8, BR_GO = 12 };

#define DBG(i)

__device__ __forceinline__ uint32_t acc_off(int c, int q, int lane) {
    return (lane & 7) * 16 + ((lane >> 3) & 1) * 256 + (lane >> 4) * 1024 + (q & 1) * 2048 + (q >> 1) * 16384 + c * 4096;
}
__device__ __forceinline__ int tile_of(int q, int i) { return i == 3 ? 3 + 8 * (q >> 1) : (q == 3 && i == 2 ? 7 : 4 * q + i); }
__device__ __forceinline__ uint32_t acc_slot(int s) { return (s & 1) * 128 + (s & 2) * 256 + (s & 4) * 8192; }

__global__ void __cluster_dims__(CLUSTER, 1, 1) __launch_bounds__(384, 1)
k_rec(const __grid_constant__ CUtensorMap mapXs, const __grid_constant__ CUtensorMap mapU, const __grid_constant__ CUtensorMap mapY, const SsmArgs ssm, const uint8_t* x, const __nv_bfloat16* __restrict__ mem0,
      const uint8_t* wk, const uint8_t* wv, unsigned ntotal, const uint32_t zero) {
    extern __shared__ __align__(1024) uint8_t smem[];
    const uint32_t sb = smem_u32(smem);
    const int tid = threadIdx.x, wid = __shfl_sync(0xffffffffu, tid >> 5, 0), w = wid & 3;
    const int h = blockIdx.x >> 2, c = blockIdx.x & 3;
    const int rk = blockIdx.x & (CLUSTER - 4);
    uint8_t* const accb = (uint8_t*)(((uintptr_t)g_ACC + 32767) & ~(uintptr_t)32767);

    asm volatile("griddepcontrol.launch_dependents;" ::: "memory");
    if (tid == 0) GT(0, 0);

    if (wid < 8) {
        asm volatile("setmaxnreg.inc.sync.aligned.u32 232;");
        if (blockIdx.x < D / 8) ssm_unit(sb, sb + R_MISC + 8, 0, true, blockIdx.x * 8, ssm, &mapU, BR_PRO, zero);
        asm volatile("fence.proxy.async.shared::cta;" ::: "memory");
        if (tid == 0) GT(0, 1);
        bar_sync(BR_ALL, 288);
        auto load_weights = [&](uint4 (&wr)[7][6], int lane) {
            wait_count_warp(g_FT + ((wid >> 2) * 32 + 2 * h + (c >> 1)) * 32 + (lane & 1), lds32(sb + R_MISC) * 32 + min(w + 1, 4 - (lane & 1)), 40);
            fence_gpu();
            const uint4* fp = g_F + ((((wid >> 2) * 16 + h) * 4 + c) * 28 + 7 * w) * 224 + lane;
            uint4 w0[7];
#pragma unroll
            for (int m = 0; m < 7; m++) w0[m] = __ldcg(fp + m * 32);
#pragma unroll
            for (int k = 0; k < 6; k++)
#pragma unroll
                for (int m = 0; m < 7; m++) wr[m][k] = __ldcg(fp + (k + 1) * 224 + m * 32);
#pragma unroll
            for (int m = 0; m < 7; m++) { const uint4 v = movm4(w0[m]); sts128(sb + R_WB + wid * WB + lane * 16 + m * 512, v.x, v.y, v.z, v.w); }
#pragma unroll
            for (int k = 0; k < 6; k++)
#pragma unroll
                for (int m = 0; m < 7; m++) wr[m][k] = movm4(wr[m][k]);
            if (wid < 3) sts128(sb + R_STG + w * STGB + S_ONE + lane * 16, ONE2, ONE2, ONE2, ONE2);
            if (wid == 4) sts128(sb + R_WB + 4 * WB + W_QRT, 0x3e803e80u, 0x3e803e80u, 0x3e803e80u, 0x3e803e80u);
            cluster_sync();
        };
        if (wid < 4) {
            asm volatile("setmaxnreg.inc.sync.aligned.u32 248;");
            const int lane = fresh_lane(), g = lane >> 2;
            const uint32_t l16 = sb + lane * 16, l8 = sb + lane * 8;
            uint4 wr[7][6];
            load_weights(wr, lane);
            const uint32_t r2 = uni(mapa(sb, 2) - mapa(sb, 0));
            const uint32_t uw = uni(R_WB + w * WB), uc = uni(R_WB + c * WB), u2 = uni((tile_of(w, 2) - 4 * w) * 128);
            const uint32_t upoll = uni(acc_off(w, 0, 0)), ured = uni(acc_off(c, w, 0)), uk = uni(S_KO + w * 1792), uv = uni(S_V + 4 * w * 512);
            const int src = 16 * (w & 1) + (lane >> 1);
            const uint32_t sia = sb + R_WB + W_SMI + (w >> 1) * 256 + src * 8;
            {
                const uint32_t ua = sb + R_WB + (4 + (lane >> 3)) * WB + W_UP + (lane & 7) * 16 + 4 * w * 128;
                sts128u<W_TAB>(l16, uw, mapa(sb + R_SMM + (w < 2 ? c * 256 + src * 8 : 1024 + c * 128 + src * 4), rk + (lane & 1)), mapa(sb + R_BAR + B_SM, rk + (lane & 1)), acc_off(0, 0, lane), 0u);
                sts128u<W_TAB + 512>(l16, uw, l8 + (((g ^ w) & 1) ? S_ONE : S_V + tile_of(w, 3) * 512), ua,
                                     ((lane ^ w) & 1) ? sb + R_WB + 4 * WB + W_QRT : ua + (tile_of(w, 3) - 4 * w) * 128,
                                     sb + R_SMM + 1024 + (lane & 7) * 16 + (lane >> 4) * 128 + ((lane >> 3) & 1) * 256);
            }
            const bool wodd = w & 1;
            uint32_t t0 = clk() - POLL_DELAY;
            uint4 ub = make_uint4(0, 0, 0, 0);
            const uint8_t* pp = accb + acc_off(w, 0, lane);
            auto put_u = [&](int sl) {
                const uint32_t l4 = add_here(l8, -sb) >> 1;
                uint8_t* p = add_here((uint8_t*)(g_U + (((sl & (RS - 1)) * 64 + blockIdx.x) * 14 + 4 * w) * 32), l4);
                stg32(p, ub.x); stg32(p + 128, ub.y); stg32(p + (int)u2, ub.z);
                if (!(((l4 >> 4) ^ w) & 1)) stg32(p + (wodd ? -128 : 384), ub.w);
            };
#pragma unroll 1
            for (int s = 0; s < NSEG; s++) {
                const uint32_t par = uni((s & 1) * 2048), bar = uni(sb + R_BAR + s * 8), stg = uni(R_STG + (s % 3) * STGB), ksa = uni(stg + uk);
                uint4 w0[7];
                auto load_w0 = [&]() {
                    w0[0] = lds128u<0>(l16, uw); w0[1] = lds128u<512>(l16, uw); w0[2] = lds128u<1024>(l16, uw); w0[3] = lds128u<1536>(l16, uw);
                    w0[4] = lds128u<2048>(l16, uw); w0[5] = lds128u<2560>(l16, uw); w0[6] = lds128u<3072>(l16, uw);
                };
                mbar_wait(bar + B_KV, 0);
                while ((int)(clk() - t0) < POLL_DELAY) {}
                DBG(0);
                uint32_t b[14]; int it = 0;
                auto take = [&](const uint4& v0, const uint4& v1, const uint4& v2, const uint4& v3) {
                    const uint32_t mn = min(min(v0.w, v1.w), v2.w), sel = 0x5410u ^ (mn & zero);
                    b[0] = v0.x; b[1] = v0.y; b[2] = v0.z ^ zero; b[3] = prmt(v0.w, v1.w, sel);
                    b[4] = v1.x; b[5] = v1.y; b[6] = v1.z ^ zero; b[7] = v3.z ^ (b[3] & zero);
                    b[8] = v2.x; b[9] = v2.y; b[10] = v2.z ^ zero; b[11] = prmt(v2.w, v3.w, sel);
                    b[12] = v3.x; b[13] = v3.y;
                    sts128u<W_MB>(l16, uw, b[0], b[1], b[2], b[3]); sts128u<W_MB + 512>(l16, uw, b[4], b[5], b[6], b[7]);
                    sts128u<W_MB + 1024>(l16, uw, b[8], b[9], b[10], b[11]); sts64u<W_MB + 1536>(l16, uw, b[12], b[13]);
                    return __all_sync(0xffffffffu, mn >= CNT16 && v3.w >= CNT16);
                };
                uint4 v0 = ld_relaxed4(pp), v1 = ld_relaxed4(pp + 2048), v2 = ld_relaxed4(pp + 16384), v3 = ld_relaxed4(pp + 18432);
                load_w0();
                const uint4 ta = lds128u<W_TAB>(l16, uw);
                uint4 k0 = lds128u<0>(l16, ksa);
                const uint4 k1 = lds128u<512>(l16, ksa), k2 = lds128u<1024>(l16, ksa);
                const uint2 k3 = lds64u<1536>(l8, ksa);
                bar_arrive(BR_POLL + w, 64);
                if (s > 0) put_u(s - 1);
                {
                    sts128u<W_TAB + 1024>(l16, uw, ta.x + par, ta.y + s * 8, ta.x + par + r2, ta.y + s * 8 + r2);
                    const uint64_t rp = (uint64_t)(accb + (acc_slot(s + 1) + ured + ta.z)), pn = (uint64_t)(accb + (acc_slot(s + 1) + upoll + ta.z));
                    sts128u<W_TAB + 1536>(l16, uw, (uint32_t)rp, (uint32_t)(rp >> 32), (uint32_t)pn, (uint32_t)(pn >> 32));
                }
                if (__any_sync(0xffffffffu, zero & (k0.y | k1.x | k2.x | k3.x | w0[0].x | w0[1].x | w0[2].x | w0[3].x | w0[4].y | w0[5].y | w0[6].x))) __trap();
                if (__builtin_expect(take(v0, v1, v2, v3), 1)) bar_sync(BR_MB, 256);
                else {
                    do {
                        if (++it > SPIN) __trap();
                        v0 = ld_relaxed4(pp); v1 = ld_relaxed4(pp + 2048); v2 = ld_relaxed4(pp + 16384); v3 = ld_relaxed4(pp + 18432);
                    } while (!take(v0, v1, v2, v3));
                    bar_sync(BR_MB + zero, 256);
                }
                DBG(1);
                float acc[7][4], sa[4], sc[4], sx[4], sy[4];
                uint32_t tb[14];
                auto T = [&](int m, int k) { if (k == 0) mmaqz(acc[m], w0[m], b[0], b[1]); else mmaq(acc[m], wr[m][k - 1], b[2 * k], b[2 * k + 1]); };
                auto TR = [&](int m) { tb[2 * m] = movm(pack_bf16(acc[m][0], acc[m][1])); tb[2 * m + 1] = movm(pack_bf16(acc[m][2], acc[m][3])); };
                auto after = [&](uint32_t v, float dep) { return v ^ (__float_as_uint(dep) & zero); };
                T(6, 0); T(0, 0); T(1, 0); T(2, 0);
                T(6, 1); T(0, 1); T(1, 1); T(3, 0);
                T(6, 2); T(0, 2); T(1, 2); T(2, 1);
                T(6, 3); T(0, 3); T(1, 3); T(3, 1);
                T(6, 4); T(0, 4); T(1, 4); T(2, 2);
                T(6, 5); T(0, 5); T(1, 5); T(3, 2);
                T(6, 6); T(0, 6); T(1, 6); T(2, 3);
                w0[4].x = after(w0[4].x, acc[6][0]); w0[5].x = after(w0[5].x, acc[6][1]);
                const uint32_t ld = after(l16, acc[6][2]);
                uint4 am0 = lds128u<W_MB>(ld, uc);
                const uint2 am3 = lds64u<W_MB + 1536>(ld, uc);
                k0.x = after(k0.x, acc[1][0]);
                DBG(2);
                T(3, 3); T(4, 0); T(5, 0); T(2, 4);
                TR(6); TR(0); TR(1);
                T(3, 4); T(4, 1); T(5, 1); T(2, 5);
                T(3, 5); T(4, 2); T(5, 2); T(2, 6);
                T(3, 6); T(4, 3); T(5, 3);
                am0.x = after(am0.x, acc[2][0]);
                const uint32_t ld2 = after(l16, acc[2][1]);
                uint4 am1 = lds128u<W_MB + 512>(ld2, uc);
                const uint4 am2 = lds128u<W_MB + 1024>(ld2, uc);
                mmaqz(sx, k0, b[0], b[1]); mmaqz(sy, k0, b[2], b[3]);
                T(4, 4); T(5, 4);
                TR(2); TR(3);
                mmaqz(sa, am0, tb[0], tb[2]); mmaqz(sc, am0, tb[1], tb[3]);
                T(4, 5); T(5, 5);
                mmaq(sx, k1, b[4], b[5]); mmaq(sy, k1, b[6], b[7]);
                T(4, 6); T(5, 6);
                mma1688(sa, am3.x, am3.y, tb[12]); mma1688(sc, am3.x, am3.y, tb[13]);
                mmaq(sx, k2, b[8], b[9]); mmaq(sy, k2, b[10], b[11]);
                am1.x = after(am1.x, acc[4][0]);
                TR(4); TR(5);
                mmaq(sa, am1, tb[4], tb[6]); mmaq(sc, am1, tb[5], tb[7]);
                mma1688(sx, k3.x, k3.y, b[12]); mma1688(sy, k3.x, k3.y, b[13]);
                sts64u<W_SMI + 256>(l8, uw, __float_as_uint(sx[0] + sy[2]), __float_as_uint(sx[1] + sy[3]));
                const uint4 ra = lds128u<W_TAB + 1024>(l16, uw);
                bar_arrive((BR_GO + w) ^ (tb[GO_DEP] & zero), 64);
                mmaq(sa, am2, tb[8], tb[10]); mmaq(sc, am2, tb[9], tb[11]);
                sts64u<W_SMI>(l8, uw, __float_as_uint(sa[0] + sc[2]), __float_as_uint(sa[1] + sc[3]));
                DBG(3);
                bar_sync(BR_SM, 128);
                {
                    const float2 p0 = lds64f(sia), p1 = lds64f(sia + WB), p2 = lds64f(sia + 2 * WB), p3 = lds64f(sia + 3 * WB);
                    const float y0 = (p0.x + p1.x) + (p2.x + p3.x), y1 = (p0.y + p1.y) + (p2.y + p3.y);
                    if (w >= 2) { const uint32_t e = pack_bf16(ex2(y0), ex2(y1)); st_async1(ra.x, ra.y, e); st_async1(ra.z, ra.w, e); }
                    else { st_async2(ra.x, ra.y, y0, y1); st_async2(ra.z, ra.w, y0, y1); }
                }
                DBG(4);
                const uint4 tc = lds128u<W_TAB + 512>(l16, uw);
                const uint4 td = lds128u<W_TAB + 1536>(l16, uw);
                const uint32_t va3 = tc.x, ua = tc.y, ua3 = tc.z, ea = tc.w;
                uint2 vb[4][2];
                auto load_v = [&]() {
                    const uint32_t va = stg + uv, va2 = va + 4 * u2;
                    vb[0][0] = lds64u<0>(l8, va); vb[1][0] = lds64u<512>(l8, va); vb[2][0] = lds64u<0>(l8, va2);
                    vb[0][1] = lds64u<256>(l8, va); vb[1][1] = lds64u<768>(l8, va); vb[2][1] = lds64u<256>(l8, va2);
                    vb[3][0] = lds64u<0>(va3, stg); vb[3][1] = lds64u<256>(va3, stg);
                };
                load_v();
                sts128u<W_TB>(l16, uw, tb[0], tb[2], tb[1], tb[3]); sts128u<W_TB + 512>(l16, uw, tb[4], tb[6], tb[5], tb[7]);
                sts128u<W_TB + 1024>(l16, uw, tb[8], tb[10], tb[9], tb[11]); sts64u<W_TB + 1536>(l8, uw, tb[12], tb[13]);
                float o[4][4];
                auto pv_x = [&](const uint4& e01, const uint4& e23) {
#pragma unroll
                    for (int q = 3; q < 7; q++) mmaqz(o[q & 3], e01, vb[q & 3][0].x, vb[q & 3][0].y);
#pragma unroll
                    for (int q = 3; q < 7; q++) mmaq(o[q & 3], e23, vb[q & 3][1].x, vb[q & 3][1].y);
                };
                uint4 u0 = ub, u1 = ub, uu = ub, u3 = ub;
                auto pv_m = [&](float f0, float f1) {
                    const uint4 pm = make_uint4(pack_bf16(f0, f1), __float_as_uint(f0), pack_bf16_again(f0, f1), __float_as_uint(f1));
                    mmaq(o[3], pm, u3.x, u3.y); mmaq(o[0], pm, u0.x, u0.y); mmaq(o[1], pm, u1.x, u1.y); mmaq(o[2], pm, uu.x, uu.y);
                    mmaq(o[3], pm, u3.z, u3.w); mmaq(o[0], pm, u0.z, u0.w); mmaq(o[1], pm, u1.z, u1.w); mmaq(o[2], pm, uu.z, uu.w);
                };
                uint4 res;
                auto finish = [&]() {
                    const float r = rcp(wodd ? o[3][0] : o[3][1]);
                    res = make_uint4(pack_bf16(o[0][0] * r, o[0][1] * r), pack_bf16(o[1][0] * r, o[1][1] * r), pack_bf16(o[2][0] * r, o[2][1] * r),
                                     pack_bf16((wodd ? o[3][1] : o[3][0]) * r, 1.0f));
                };
                mbar_wait_cl(bar + B_SM);
                DBG(5);
                float x0, x1;
                {
                    const uint4 e = ldsm4tu<0>(ea, par);
                    const float2 p0 = lds64fu<R_SMM>(l8, par), p1 = lds64fu<R_SMM + 256>(l8, par), p2 = lds64fu<R_SMM + 512>(l8, par), p3 = lds64fu<R_SMM + 768>(l8, par);
                    x0 = (p0.x + p1.x) + (p2.x + p3.x); x1 = (p0.y + p1.y) + (p2.y + p3.y);
                    pv_x(e, make_uint4(e.y ^ zero, __float_as_uint(x0), e.w ^ zero, __float_as_uint(x1)));
                }
                DBG(6);
                bar_sync(BR_UP, 256);
                u3 = ldsm4q(ua3); u0 = ldsm4q(ua); u1 = ldsm4q(ua + 128); uu = ldsm4u<0>(ua, u2);
                pv_m(ex2(x0), ex2(x1));
                finish();
                if (__builtin_expect(__any_sync(0xffffffffu, __float_as_uint(wodd ? o[3][0] : o[3][1]) - SAFE_LO >= SAFE_SPAN), 0)) {
                    float y[8];
#pragma unroll
                    for (int q = 0; q < 8; q++) {
                        const uint32_t ln = add_here(l8, -sb) >> 3;
                        const uint32_t a = mapa(sb + R_WB + W_SMI + 256 + (2 * (ln & 3) + (q & 1)) * 32 + (ln >> 2) * 4, rk + (q >> 1));
                        y[q] = (ldr32f(a) + ldr32f(a + WB)) + (ldr32f(a + 2 * WB) + ldr32f(a + 3 * WB));
                    }
                    float m = fmaxf(x0, x1);
#pragma unroll
                    for (int q = 0; q < 8; q++) m = fmaxf(m, y[q]);
                    m = fmaxf(m, __shfl_xor_sync(0xffffffffu, m, 1)); m = fmaxf(m, __shfl_xor_sync(0xffffffffu, m, 2));
                    load_v();
                    pv_x(make_uint4(pack_bf16(ex2(y[0] - m), ex2(y[1] - m)), 0u, pack_bf16(ex2(y[2] - m), ex2(y[3] - m)), 0u),
                         make_uint4(pack_bf16(ex2(y[4] - m), ex2(y[5] - m)), 0u, pack_bf16(ex2(y[6] - m), ex2(y[7] - m)), 0u));
                    pv_m(ex2(x0 - m), ex2(x1 - m));
                    finish();
                }
                DBG(8);
                red_bf16x8((void*)(((uint64_t)td.y << 32) | td.x), res.x, res.y, res.z, res.w);
                t0 = clk();
                DBG(9);
                bar_arrive(BR_RED, 256);
                SCHED_FENCE(zero, 5);
                pp = (const uint8_t*)(((uint64_t)td.w << 32) | td.z);
                ub = make_uint4(hsum4(u0.x, u0.y, u0.z, u0.w), hsum4(u1.x, u1.y, u1.z, u1.w), hsum4(uu.x, uu.y, uu.z, uu.w), hsum4(u3.x, u3.y, u3.z, u3.w));
            }
            bar_arrive(BR_POLL + w, 64);
            put_u(NSEG - 1);
            bar_arrive(BR_PRO, 160);
        } else {
            const int lane = fresh_lane(), g = lane >> 2, t = lane & 3;
            const uint32_t l16 = sb + lane * 16, l8 = sb + lane * 8, wsa = l16 + R_WB + wid * WB;
            uint4 wr[7][6];
            load_weights(wr, lane);
            uint32_t* pdst = g_P + (h * 14 + (c * (c + 3) >> 1)) * 32 + lane;
            const uint32_t xa = sb + S_X + (lane & 15) * 240;
            auto softmax_rows = [&](int sl, bool gate) {
                mbar_wait_cl(sb + R_BAR + B_LS + sl * 8);
                const uint32_t a = R_LS + (sl & 1) * 5120;
                const float4 q0 = sum4(lds128f(l16 + a), lds128f(l16 + a + 1280), lds128f(l16 + a + 2560), lds128f(l16 + a + 3840));
                float4 q1 = make_float4(0.f, 0.f, 0.f, 0.f);
                q1 = sum4(lds128f(l16 + a + 512), lds128f(l16 + a + 1792), lds128f(l16 + a + 3072), lds128f(l16 + a + 4352));
                const float2 p0 = lds64f(l8 + a + 1024), p1 = lds64f(l8 + a + 2304), p2 = lds64f(l8 + a + 3584), p3 = lds64f(l8 + a + 4864);
                float v[10] = {q0.x, q0.y, q0.z, q0.w, q1.x, q1.y, q1.z, q1.w, (p0.x + p1.x) + (p2.x + p3.x), (p0.y + p1.y) + (p2.y + p3.y)};
                const int lim = 8 * c + g - 2 * t;
#pragma unroll
                for (int i = 0; i < 8; i++) v[i] = (8 * (i >> 1) + (i & 1) <= lim) ? v[i] : -INFINITY;
                float e[10], l[4];
                auto expo = [&](float m) {
#pragma unroll
                    for (int i = 0; i < 10; i++) e[i] = ex2(v[i] - m);
                    mma16816z(l, pack_bf16(e[0], e[1]), pack_bf16(e[4], e[5]), pack_bf16(e[2], e[3]), pack_bf16(e[6], e[7]), ONE2, ONE2);
                    mma1688(l, pack_bf16(e[8], e[9]), 0u, ONE2);
                    l[0] += l[2];
                };
                expo(0.f);
                if (__builtin_expect(__any_sync(0xffffffffu, __float_as_uint(l[0]) - SAFE_LO >= SAFE_SPAN), 0)) {
                    float m = v[0];
#pragma unroll
                    for (int i = 1; i < 10; i++) m = fmaxf(m, v[i]);
                    m = fmaxf(m, __shfl_xor_sync(0xffffffffu, m, 1)); m = fmaxf(m, __shfl_xor_sync(0xffffffffu, m, 2));
                    expo(m);
                }
                const float r = rcp(l[0]);
                uint32_t* pd = pdst + (sl & (RS - 1)) * (16 * 448);
                if (gate) bar_sync((BR_POLL + w) ^ (__float_as_uint(r) & zero), 64);
#pragma unroll
                for (int q = 0; q < 4; q++) if (q <= c) pd[q * 32] = pack_bf16(e[2 * q] * r, e[2 * q + 1] * r);
                pd[(c + 1) * 32] = pack_bf16(e[8] * r, e[9] * r);
            };
            auto publish = [&](int sl) {
                __syncwarp();
                if (lane == 0) mbar_arrive(sb + R_BAR + B_PUB + sl * 8);
                if (sl >= 2) mbar_wait(sb + R_BAR + B_Z + (sl - 2) * 8, 0);
            };
            bar_sync(BR_POLL + w, 64);
#pragma unroll 1
            for (int s = 0; s < NSEG; s++) {
                const uint32_t stg = R_STG + (s % 3) * STGB;
                uint4 w0[7];
#pragma unroll
                for (int m = 0; m < 7 - UW0; m++) w0[m] = lds128(wsa + m * 512);
                bar_sync(BR_MB, 256);
                mbar_arrive_if(lane + w == 0, sb + R_BAR + B_H + s * 8);
                const uint32_t ba = wsa - 4 * WB + W_MB;
                const uint4 b0 = lds128(ba), b1 = lds128(ba + 512), b2 = lds128(ba + 1024);
                const uint2 b3 = lds64(ba + 1536);
#pragma unroll
                for (int m = 7 - UW0; m < 7; m++) w0[m] = lds128(wsa + m * 512);
                bar_sync(BR_GO + w, 64);
                SCHED_FENCE(zero, 2);
                DBG(11);
                float acc[7][4];
                const uint32_t b[14] = {b0.x, b0.y, b0.z, b0.w, b1.x, b1.y, b1.z, b1.w, b2.x, b2.y, b2.z, b2.w, b3.x, b3.y};
                auto U = [&](int m, int k) { if (k == 0) mmaqz(acc[m], w0[m], b[0], b[1]); else mmaq(acc[m], wr[m][k - 1], b[2 * k], b[2 * k + 1]); };
#pragma unroll
                for (int k = 0; k < 7; k++)
#pragma unroll
                    for (int m = 0; m < 7; m++) U(m, k);
                {
                    const uint32_t a = wsa + W_UP;
#pragma unroll
                    for (int q = 0; q < 3; q++)
                        stsm4(a + q * 512, make_uint4(pack_bf16(acc[2 * q][0], acc[2 * q][1]), pack_bf16(acc[2 * q][2], acc[2 * q][3]),
                                                      pack_bf16(acc[2 * q + 1][0], acc[2 * q + 1][1]), pack_bf16(acc[2 * q + 1][2], acc[2 * q + 1][3])));
                    stsm2(a + 1536, pack_bf16(acc[6][0], acc[6][1]), pack_bf16(acc[6][2], acc[6][3]));
                }
                bar_arrive(BR_UP, 256);
                DBG(12);
                bar_sync(BR_RED, 256);
                if (w == 1) { if (s > 0) softmax_rows(s - 1, true); else bar_sync(BR_POLL + w, 64); }
                else {
                    const uint32_t dst = R_LS + (s & 1) * 5120 + c * 1280, lb = R_BAR + B_LS + s * 8;
                    const uint32_t xs = xa + stg + (lane >> 4) * 32, x6 = xa + stg + (lane >> 4) * 16 + 192;
                    const uint32_t r0 = mapa(sb, rk), r1 = mapa(sb, rk + 1), r2 = mapa(sb, rk + 2), r3 = mapa(sb, rk + 3);
                    auto X = [&](int mt, int k) { return ldsm4q(k == 6 ? x6 + mt * 3840 : xs + mt * 3840 + (k >> 1) * 64 + (k & 1) * 16); };
                    float y[4][4];
                    if (w == 0) {
                        uint32_t f[14];
#pragma unroll
                        for (int q = 0; q < 3; q++) {
                            const uint32_t a = l16 + R_WB + W_TB + q * 512;
                            const uint4 p0 = lds128(a), p1 = lds128(a + WB), p2 = lds128(a + 2 * WB), p3 = lds128(a + 3 * WB);
                            f[4 * q] = hsum4(p0.x, p1.x, p2.x, p3.x); f[4 * q + 1] = hsum4(p0.y, p1.y, p2.y, p3.y);
                            f[4 * q + 2] = hsum4(p0.z, p1.z, p2.z, p3.z); f[4 * q + 3] = hsum4(p0.w, p1.w, p2.w, p3.w);
                        }
                        const uint32_t a = l8 + R_WB + W_TB + 1536;
                        const uint2 p0 = lds64(a), p1 = lds64(a + WB), p2 = lds64(a + 2 * WB), p3 = lds64(a + 3 * WB);
                        f[12] = hsum4(p0.x, p1.x, p2.x, p3.x); f[13] = hsum4(p0.y, p1.y, p2.y, p3.y);
#pragma unroll
                        for (int k = 0; k < 7; k++)
#pragma unroll
                            for (int mt = 0; mt < 2; mt++) {
                                if (k < 2) mmaqz(y[2 * mt + k], X(mt, k), f[2 * k], f[2 * k + 1]); else mmaq(y[2 * mt + (k & 1)], X(mt, k), f[2 * k], f[2 * k + 1]);
                            }
                        const uint32_t o = dst + 1024 + lane * 8;
                        bar_sync((BR_POLL + w) ^ (__float_as_uint(y[2][0]) & zero), 64);
                        st_async2(r0 + o, r0 + lb, y[0][0] + y[1][0], y[0][1] + y[1][1]); st_async2(r1 + o, r1 + lb, y[0][2] + y[1][2], y[0][3] + y[1][3]);
                        st_async2(r2 + o, r2 + lb, y[2][0] + y[3][0], y[2][1] + y[3][1]); st_async2(r3 + o, r3 + lb, y[2][2] + y[3][2], y[2][3] + y[3][3]);
                    } else {
                        const uint32_t ka = stg + S_KS + (w == 3 ? 3584 : 0);
                        uint32_t f[2][14];
#pragma unroll
                        for (int j = 0; j < 2; j++) {
#pragma unroll
                            for (int q = 0; q < 3; q++) { const uint4 v = lds128(l16 + ka + j * 1792 + q * 512); f[j][4 * q] = v.x; f[j][4 * q + 1] = v.y; f[j][4 * q + 2] = v.z; f[j][4 * q + 3] = v.w; }
                            const uint2 v = lds64(l8 + ka + j * 1792 + 1536); f[j][12] = v.x; f[j][13] = v.y;
                        }
                        if (w == 2) {
#pragma unroll
                            for (int k = 0; k < 7; k++)
#pragma unroll
                                for (int mt = 0; mt < 2; mt++) {
                                    const uint4 a = X(mt, k);
                                    if (k == 0) { mmaqz(y[2 * mt], a, f[0][0], f[0][1]); mmaqz(y[2 * mt + 1], a, f[1][0], f[1][1]); }
                                    else { mmaq(y[2 * mt], a, f[0][2 * k], f[0][2 * k + 1]); mmaq(y[2 * mt + 1], a, f[1][2 * k], f[1][2 * k + 1]); }
                                }
                            const uint32_t o = dst + lane * 16;
                            bar_sync((BR_POLL + w) ^ (__float_as_uint(y[3][0]) & zero), 64);
                            st_async4(r0 + o, r0 + lb, y[0][0], y[0][1], y[1][0], y[1][1]); st_async4(r1 + o, r1 + lb, y[0][2], y[0][3], y[1][2], y[1][3]);
                            st_async4(r2 + o, r2 + lb, y[2][0], y[2][1], y[3][0], y[3][1]); st_async4(r3 + o, r3 + lb, y[2][2], y[2][3], y[3][2], y[3][3]);
                        } else {
#pragma unroll
                            for (int k = 0; k < 7; k++) {
                                const uint4 a = X(1, k);
                                if (k < 2) { mmaqz(y[k], a, f[0][2 * k], f[0][2 * k + 1]); mmaqz(y[2 + k], a, f[1][2 * k], f[1][2 * k + 1]); }
                                else { mmaq(y[k & 1], a, f[0][2 * k], f[0][2 * k + 1]); mmaq(y[2 + (k & 1)], a, f[1][2 * k], f[1][2 * k + 1]); }
                            }
                            const uint32_t o = dst + 512 + lane * 16;
                            bar_sync((BR_POLL + w) ^ (__float_as_uint(y[2][0]) & zero), 64);
                            st_async4(r2 + o, r2 + lb, y[0][0] + y[1][0], y[0][1] + y[1][1], y[2][0] + y[3][0], y[2][1] + y[3][1]);
                            st_async4(r3 + o, r3 + lb, y[0][2] + y[1][2], y[0][3] + y[1][3], y[2][2] + y[3][2], y[2][3] + y[3][3]);
                        }
                    }
                }
                DBG(13);
                if (w == 1 && s > 0) publish(s - 1);
                DBG(14);
            }
            if (w == 1) softmax_rows(NSEG - 1, false);
            if (w == 1) { bar_sync(BR_PRO, 160); publish(NSEG - 1); }
        }
        cluster_sync();
    } else {
        asm volatile("setmaxnreg.dec.sync.aligned.u32 24;");
        const unsigned epoch = uni(ld_relaxed(&g_EXIT) / ntotal);
        const int lane = fresh_lane();
        if (elect_one()) {
#pragma unroll 1
            for (int i = w; i < 384; i += 4) {
                mbar_init(sb + R_BAR + i * 8, 1);
                if (i < 192) mbar_expect(sb + R_BAR + i * 8, i < 64 ? S_ONE : (i < 128 ? 1536 : (c < 2 ? 3072 : 5120)));
            }
            asm volatile("fence.mbarrier_init.release.cluster;" ::: "memory");
            asm volatile("fence.proxy.async.shared::cta;" ::: "memory");
        }
        __syncwarp();
        bar_sync(BR_H, 128);
        if (w == 0) {
            sts32(sb + R_MISC, epoch);
            wait_count_warp(&g_INIT, (epoch + 1) * 64, 100);
            fence_gpu();
            bar_sync(BR_ALL, 288);
            asm volatile("barrier.cluster.arrive.relaxed.aligned;" ::: "memory");
            const unsigned* ft = g_FT + (lane < 2 ? 2 * h + lane : 32 + 2 * h + (c >> 1)) * 32;
#pragma unroll 1
            for (int seg = 0; seg < NSEG; seg++) {
                if (!(seg & 1)) {
                    wait_count_warp(ft + (~(seg >> 1) & 1), epoch * 32 + (((seg >> 1) + 9) >> 1), seg ? 0 : 40);
                    fence_gpu();
                    asm volatile("fence.proxy.async.global;" ::: "memory");
                }
                const uint32_t bar = sb + R_BAR + B_KV + seg * 8, dst = sb + R_STG + (seg % 3) * STGB;
                const uint8_t* kp = g_K + ((seg & (RS - 1)) * 16 + h) * 28672;
                const uint8_t* vp = g_V + (((seg & (RS - 1)) * 16 + h) * 4 + c) * 7168;
                if (lane == 0 && seg == 0) GT(0, 7);
                if (seg >= 2) mbar_wait(sb + R_BAR + B_H + (seg - 2) * 8, 0);
                if (elect_one()) {
                    bulk_g2s(dst + S_KO, kp + c * 7168, 7168, bar);
                    bulk_g2s(dst + S_V, vp, 7168, bar);
                    tma2d(dst + S_X, &mapXs, 112 * c, 32 * seg, bar);
#pragma unroll
                    for (int j = 0; j < 4; j++) bulk_g2s(dst + S_KS + j * 1792, kp + j * 7168 + c * 1792, 1792, bar);
                }
                if (lane == 0 && seg == 2) GT(0, 4);
                if (lane == 0 && seg == NSEG - 1) GT(0, 5);
                if (seg == 1) asm volatile("barrier.cluster.wait.aligned;" ::: "memory");
            }
        } else if (w == 1) {
            {
                const int q = h >> 2, l = (h & 3) * 8 + (lane & 7);
                const uint32_t* mp = (const uint32_t*)(mem0 + (l >> 2) * D + 112 * c) + (l & 3);
                uint4 v = make_uint4(0, 0, 0, 0);
                if (lane < 8) v = make_uint4(mp[4 * tile_of(q, 0)], mp[4 * tile_of(q, 1)], mp[4 * tile_of(q, 2)],
                                             ((mp[4 * tile_of(q, 3)] >> (16 * (q & 1))) & 0xffffu) | CNT16);
                *(uint4*)(accb + acc_off(c, q, l) + acc_slot(lane >> 3)) = v;
                *(uint4*)(accb + acc_off(c, q, l) + acc_slot(4 + (lane >> 3))) = make_uint4(0, 0, 0, 0);
                __syncwarp();
                if (lane == 0) { fence_gpu(); red_inc(&g_INIT); }
            }
            __syncwarp();
            cluster_sync();
            if (lane == 0) GT(0, 3);
            uint8_t* zp = accb + acc_off(c, h >> 2, (h & 3) * 8 + (lane & 7));
#pragma unroll 1
            for (int seg = 0; seg < NSEG; seg++) {
                mbar_wait(sb + R_BAR + B_PUB + seg * 8, 0);
                if (lane < 8 && seg < NSEG - 8) *(uint4*)(zp + acc_slot(seg)) = make_uint4(0, 0, 0, 0);
                __syncwarp();
                if (lane == 0) {
                    fence_gpu();
                    red_inc(g_CNT + seg * 32); mbar_arrive(sb + R_BAR + B_Z + seg * 8); }
                __syncwarp();
            }
            if (lane == 0) GT(0, 6);
        } else {
            if (w == 2 && PF2) {
                const uint32_t t1 = clk();
                while ((int)(clk() - t1) < PF2) __nanosleep(100);
                if (elect_one()) {
#pragma unroll 1
                    for (int i = 1; i < 7; i++) { prefetch_l2(wk + (i * 64 + blockIdx.x) * 8192, 8192); prefetch_l2(wv + (i * 64 + blockIdx.x) * 8192, 8192); }
                    prefetch_l2(x + blockIdx.x * 28672, 28672);
                }
            }
            cluster_sync();
            if (w == 3 && blockIdx.x < D / 8) {
#pragma unroll 1
                for (int i = 0; i < 16; i++) {
                    mbar_wait(sb + R_BAR + B_H + i * 8, 0);
                    if (elect_one()) { ssm_store(sb, blockIdx.x * 8, i, &mapY); asm volatile("cp.async.bulk.wait_group 0;" ::: "memory"); }
                    __syncwarp();
                }
            }
        }
        cluster_sync();
        if (w == 1 && lane == 0) red_inc(&g_EXIT);
    }
}

constexpr int BLK = 28672;
#define NRING 6
constexpr int G_RING = 7 * BLK;
constexpr int G_SCR = G_RING + NRING * 4096;
constexpr int G_BAR = G_SCR + 6144;
constexpr int G_PUB = G_BAR + 18 * 8;
constexpr int G_RDY = G_PUB + 39 * 8;
constexpr int G_MISC = G_RDY + 8 * 8;
constexpr int G_SMEM = G_MISC + 16;
static_assert(G_SMEM <= 232448, "smem");
#define FPACE 70
#define PACE 120
constexpr int LAG = 4;
static_assert(LAG + 3 <= RS / 2, "ring");

__device__ __forceinline__ void pace(uint32_t& t0, int gap) { uint32_t t1; do { t1 = clk(); } while ((int)(t1 - t0) < 0); t0 = t1 + gap; }

template <int NSTG>
__device__ __forceinline__ void tile_mainloop(float* d, uint32_t sb, int slot, uint32_t par, uint64_t db, uint32_t kstep, bool trans,
                                              int lane, int pass_to, bool wait_b) {
    const uint64_t da0 = sdesc(sb + G_RING, 16, 512, 2);
    const uint32_t eb = mapa(sb + G_BAR + 7 * 8, lane & 1);
    int prev = 0;
#pragma unroll
    for (int i = 0; i < NSTG; i++) {
        if (!(i & 1) && wait_b) mbar_wait(sb + G_BAR + (14 + (i >> 1)) * 8, 0);
        mbar_wait(sb + G_BAR + slot * 8, par);
        wg_fence();
        const uint64_t da = da0 + slot * 256, b0 = db + (i >> 1) * (BLK >> 4) + (i & 1) * 2 * kstep;
        if (trans) { wgmma224<1>(d, da, b0, i); wgmma224<1>(d, da + 2, b0 + kstep, 1); }
        else { wgmma224<0>(d, da, b0, i); wgmma224<0>(d, da + 2, b0 + kstep, 1); }
        wg_commit();
        if (i == NSTG - 1 && pass_to) bar_arrive(pass_to, 256);
        if (i > 0) { wg_wait<1>(); mbar_arrive_cl_if(lane < 2, eb + prev * 8); }
        prev = slot;
        if (++slot == NRING) { slot = 0; par ^= 1; }
    }
    wg_wait<0>();
    mbar_arrive_cl_if(lane < 2, eb + prev * 8);
}

template <int M>
__device__ __forceinline__ void fold_role(uint32_t sb, int n, int wg, int u, int lane) {
    const bool lead = lane == 0;
    const uint64_t db = M == 0 ? sdesc(sb + 3 * BLK, 16, 1024, 1) : sdesc(sb + 3 * BLK, 4096, 512, 2);
    const uint32_t sa = sb + (8 * ((lane >> 3) & 1) + (lane & 7)) * 128 + (((2 * u + (lane >> 4)) ^ (lane & 7)) << 4);
    uint4* dst = g_F + (n * 56 + 4 * wg + u) * 224 + lane;
    uint4 q[14], qa[14];
#pragma unroll
    for (int i = 0; i < 14; i++) q[i] = make_uint4(0, 0, 0, 0);
    int blk = wg;
#pragma unroll 1
    for (;; blk += 2, dst += 8 * 224) {
        float d[112];
        bar_sync(1 + wg, 256);
        tile_mainloop<8>(d, sb, (8 * blk) % NRING, ((8 * blk) / NRING) & 1, db, M == 0 ? 2 : 64, M == 1, lane, 2 - wg, blk < 2);
        if (u == 0 && lead) GT(1, 6 + blk);
        const float sc = M ? 1.f : 0.0625f * LOG2E;
#pragma unroll
        for (int i = 0; i < 14; i++) {
            const float* e = d + 8 * i;
            qa[i] = q[i];
            q[i] = make_uint4(pack_bf16(e[0] * sc, e[1] * sc), pack_bf16(e[4] * sc, e[5] * sc), pack_bf16(e[2] * sc, e[3] * sc), pack_bf16(e[6] * sc, e[7] * sc));
        }
        auto handover = [&]() {
            bar_sync(3, 256);
#pragma unroll
            for (int i = 0; i < 14; i++) { stsm4t(sa + (blk - 2) * BLK + i * 2048, qa[i]); stsm4t(sa + blk * BLK + i * 2048, q[i]); }
            asm volatile("fence.proxy.async.shared::cta;" ::: "memory");
            bar_sync(3, 256);
        };
        if (blk == 6) { handover(); if (u == 0 && lead) GT(1, 13); }
        uint32_t t0 = clk();
#pragma unroll
        for (int i = 0; i < 14; i++) {
            pace(t0, FPACE);
            dst[(i / 7) * (28 * 224) + (i % 7) * 32] = q[i];
            if (blk < 3) stsm4t(sa + blk * BLK + i * 2048, q[i]);
        }
        __syncwarp();
        mbar_arrive_if(lead, sb + G_PUB + blk * 8);
        if (blk == 5) handover();
        if (blk >= 5) break;
    }
}

__device__ __forceinline__ void bulk_consumer(uint32_t sb, int n, unsigned epoch, __nv_bfloat16* __restrict__ out, int phases) {
    const int lane = fresh_lane(), wid = __shfl_sync(0xffffffffu, threadIdx.x >> 5, 0), wg = wid >> 2, u = wid & 3;
    const int h = (n >> 1) & 15, hf = n & 1;
    const bool lead = lane == 0;
    if (phases & 1) {
        if (wg == 1) bar_arrive(1, 256);
        if (n < 32) fold_role<0>(sb, n, wg, u, lane); else fold_role<1>(sb, n, wg, u, lane);
        bar_sync(1 + wg, 256);
    }
    const uint64_t db = sdesc(sb, 16, 1024, 1);
    float acc[2][7][4];
#pragma unroll
    for (int i = 0; i < 56; i++) (&acc[0][0][0])[i] = 0.f;
#pragma unroll 1
    for (int tile = 1 - wg; tile < LAG + 36; tile += 2) {
        const bool gemm = tile < 32 && (phases & 1);
        uint32_t y[56];
        if (gemm) {
            float d[112];
            tile_mainloop<14>(d, sb, (56 + 14 * tile) % NRING, ((56 + 14 * tile) / NRING) & 1, db, 2, false, lane, tile == 31 ? 0 : 2 - wg, false);
#pragma unroll
            for (int i = 0; i < 56; i++) y[i] = pack_bf16(d[2 * i], d[2 * i + 1]);
        } else {
#pragma unroll
            for (int i = 0; i < 56; i++) y[i] = 0;
        }
        const int rel = tile - LAG - (n >> 4), unit = n + 64 * (rel >> 2);
        const bool mine = !(rel & 1) && rel >= 0 && (phases & 2), batch = mine && rel < 32;
        uint2 v[2][14]; uint32_t p[2][14], m[2][7];
        if (batch) {
            if (!(rel & 2)) mbar_wait(sb + G_RDY + (rel >> 2) * 8, 0);
            const int sh = ((unit >> 3) & (RS - 1)) * 16 + 4 * u + (rel & 2), tl = 7 * (unit & 7);
            const uint8_t* vp = g_V + (sh * 56 + tl) * 512 + lane * 8;
            const uint32_t* up = g_U + (sh * 56 + tl) * 32 + lane;
            const uint32_t* pp = g_P + sh * 448 + lane;
#pragma unroll
            for (int j = 0; j < 2; j++) {
#pragma unroll
                for (int i = 0; i < 14; i++) { v[j][i] = __ldcg((const uint2*)(vp + j * (56 * 512) + i * 256)); p[j][i] = __ldcg(pp + j * 448 + i * 32); }
#pragma unroll
                for (int i = 0; i < 7; i++) m[j][i] = __ldcg(up + j * (56 * 32) + i * 32);
            }
        } else {
#pragma unroll
            for (int j = 0; j < 2; j++) {
#pragma unroll
                for (int i = 0; i < 14; i++) { v[j][i] = make_uint2(0u, 0u); p[j][i] = 0u; if (i < 7) m[j][i] = 0u; }
            }
        }
        if (gemm) {
            const int slot = (2 * tile + (u >> 1)) & (RS - 1);
            if (tile >= RS / 2)
                wait_count_warp(n < 32 ? g_CNT + (2 * tile + 1 - RS) * 32 : g_WD + (tile - RS / 2) * 32, (epoch + 1) * 64, 100);
            uint32_t t0 = clk();
            const int gap = tile > 1 ? PACE : FPACE;
            if (n < 32) {
                uint8_t* rec = g_K + (((slot * 16 + h) * 4 + 2 * (u & 1)) * 4 + 2 * hf) * 1792;
#pragma unroll
                for (int wq = 0; wq < 2; wq++) {
#pragma unroll
                    for (int q = 0; q < 3; q++) {
                        const uint32_t* e = y + 28 * wq + 8 * q;
                        pace(t0, gap);
                        *(uint4*)(rec + wq * 1792 + q * 512 + lane * 16) = make_uint4(e[0], e[4], e[2], e[6]);
                        pace(t0, gap);
                        *(uint4*)(rec + 7168 + wq * 1792 + q * 512 + lane * 16) = make_uint4(e[1], e[5], e[3], e[7]);
                    }
                    const uint32_t* e = y + 28 * wq + 24;
                    pace(t0, gap);
                    *(uint2*)(rec + wq * 1792 + 1536 + lane * 8) = make_uint2(e[0], e[2]);
                    *(uint2*)(rec + 7168 + wq * 1792 + 1536 + lane * 8) = make_uint2(e[1], e[3]);
                }
            } else {
                uint8_t* rec = g_V + ((slot * 16 + h) * 56 + 28 * hf) * 512 + (u & 1) * 256 + lane * 8;
#pragma unroll
                for (int i = 0; i < 28; i++) {
                    if (!(i & 1)) pace(t0, gap);
                    *(uint2*)(rec + i * 512) = make_uint2(movm(y[2 * i]), movm(y[2 * i + 1]));
                }
            }
            __syncwarp();
            mbar_arrive_if(lead, sb + G_PUB + (7 + tile) * 8);
        }
        if (mine && !(rel & 2) && rel >= 4 && rel <= 32) {
            const int pu = unit - 64;
            uint32_t* o = (uint32_t*)(out + (size_t)((pu >> 3) * 32 + 8 * u + (lane >> 2)) * OUTW + D + 56 * (pu & 7)) + (lane & 3);
            const uint32_t sc = sb + G_SCR + lane * 16;
#pragma unroll
            for (int i = 0; i < 7; i += 2) {
                const int i1 = i < 6 ? i + 1 : i;
                float4 own = make_float4(0.f, 0.f, 0.f, 0.f);
#pragma unroll
                for (int r = 0; r < 4; r++) {
                    const float* a = acc[r >> 1][i] + 2 * (r & 1); const float* b = acc[r >> 1][i1] + 2 * (r & 1);
                    if (r == u) own = make_float4(a[0], a[1], b[0], b[1]);
                    else sts128(sc + (r * 3 + ((u - r - 1) & 3)) * 512, __float_as_uint(a[0]), __float_as_uint(a[1]), __float_as_uint(b[0]), __float_as_uint(b[1]));
                }
                bar_sync(4, 128);
                const float4 z = sum4(own, lds128f(sc + u * 1536), lds128f(sc + u * 1536 + 512), lds128f(sc + u * 1536 + 1024));
                bar_sync(4, 128);
                o[4 * i] = pack_bf16(z.x, z.y);
                if (i < 6) o[4 * i + 4] = pack_bf16(z.z, z.w);
            }
#pragma unroll
            for (int i = 0; i < 56; i++) (&acc[0][0][0])[i] = 0.f;
        }
        if (tile < 30 && (phases & 1)) bar_sync(1 + wg, 256);
        if (batch) {
#pragma unroll
            for (int j = 0; j < 2; j++) {
                const uint32_t* q = p[j];
#pragma unroll
                for (int i = 0; i < 7; i++) mma16816(acc[1][i], q[5], q[9], q[6], q[10], v[j][2 * i].x, v[j][2 * i].y);
#pragma unroll
                for (int i = 0; i < 7; i++) mma16816(acc[0][i], q[0], q[2], 0u, q[3], v[j][2 * i].x, v[j][2 * i].y);
#pragma unroll
                for (int i = 0; i < 7; i++) mma16816(acc[1][i], q[7], q[11], 0u, q[12], v[j][2 * i + 1].x, v[j][2 * i + 1].y);
            }
#pragma unroll
            for (int i = 0; i < 7; i++) { mma16816(acc[0][i], p[0][1], p[0][4], p[1][1], p[1][4], m[0][i], m[1][i]); mma16816(acc[1][i], p[0][8], p[0][13], p[1][8], p[1][13], m[0][i], m[1][i]); }
            if ((rel & 2) && lead) red_inc(g_WD + (unit >> 4) * 32 + (__float_as_uint(acc[1][6][0]) & (phases >> 8)));
        }
    }
}

__global__ void __cluster_dims__(2, 1, 1) __launch_bounds__(384, 1)
k_bulk(const __grid_constant__ CUtensorMap mapX, const __grid_constant__ CUtensorMap mapK, const __grid_constant__ CUtensorMap mapV,
       const __grid_constant__ CUtensorMap mapQ, const __grid_constant__ CUtensorMap mapO, __nv_bfloat16* __restrict__ out, unsigned ntotal, int phases) {
    extern __shared__ __align__(1024) uint8_t smem[];
    const uint32_t sb = smem_u32(smem);
    const int n = blockIdx.x, wid = __shfl_sync(0xffffffffu, threadIdx.x >> 5, 0);
    if (threadIdx.x == 0) GT(1, 0);
    if (elect_one()) {
        if (wid >= 8) {
            const int i = wid - 8, h = (n >> 1) & 15, hf = n & 1;
            const uint32_t bar = sb + G_BAR + (14 + i) * 8;
            mbar_init(bar, 1);
            asm volatile("fence.proxy.async.shared::cta;" ::: "memory");
            if (n < 64 && (phases & 1)) {
                mbar_expect(bar, BLK);
                if (n < 32) tma2d(sb + (3 + i) * BLK, &mapQ, h * DH + 64 * i, 224 * hf, bar);
                else tma3d(sb + (3 + i) * BLK, &mapO, 0, h * DH + 64 * i, 7 * hf, bar);
            }
        } else {
            if (wid < 7) { mbar_init(sb + G_BAR + wid * 8, 1); mbar_init(sb + G_BAR + (7 + wid) * 8, 8); }
            asm volatile("fence.mbarrier_init.release.cluster;" ::: "memory");
            asm volatile("fence.proxy.async.shared::cta;" ::: "memory");
        }
    }
    __syncwarp();
    cluster_sync();
    if (wid < 8) {
        asm volatile("setmaxnreg.inc.sync.aligned.u32 240;");
        if (elect_one()) {
#pragma unroll 1
            for (int i = wid; i < 47; i += 8) mbar_init(sb + G_PUB + i * 8, i < 39 ? 4 : 1);
        }
        const unsigned epoch = uni(ld_relaxed(&g_EXIT) / ntotal);
        bar_sync(5, 352);
        if (n < 64) bulk_consumer(sb, n, epoch, out, phases);
        if (wid == 0 && elect_one()) GT(1, 5);
        cluster_sync();
    } else {
        asm volatile("setmaxnreg.dec.sync.aligned.u32 24;");
        unsigned epoch = 0;
        if (wid > 8) { epoch = uni(ld_relaxed(&g_EXIT) / ntotal); bar_sync(5, 352); }
        if (wid == 9 && elect_one()) red_inc(&g_EXIT);
        if (n < 64) {
            if (wid == 8) {
                if (phases & 1) {
                    const int h = (n >> 1) & 15;
                    int slot = 0; uint32_t par = 1;
#pragma unroll 1
                    for (int tile = 0; tile < 39; tile++) {
                        const CUtensorMap* map = tile >= 7 ? &mapX : (n < 32 ? &mapK : &mapV);
                        const int x0 = tile >= 7 ? 0 : h * DH, y = 64 * (tile >= 7 ? tile - 7 : tile) + 32 * (n & 1), ns = tile >= 7 ? 14 : 8;
#pragma unroll 1
                        for (int i = 0; i < ns; i++) {
                            mbar_wait(sb + G_BAR + (7 + slot) * 8, par);
                            if (elect_one()) {
                                mbar_expect(sb + G_BAR + slot * 8, 4096);
                                tma2d_pair(sb + G_RING + slot * 4096 + (n & 1) * 2048, map, x0 + 32 * i, y, sb + G_BAR + slot * 8);
                            }
                            if (++slot == NRING) { slot = 0; par ^= 1; }
                        }
                    }
                }
            } else if (wid == 9) {
                if (phases & 2) {
#pragma unroll 1
                    for (int k = 0; k < 8; k++) {
                        wait_count_warp(g_CNT + ((n >> 3) + 8 * k) * 32, (epoch + 1) * 64, k < 7 ? 200 : 20);
                        fence_gpu();
                        if (elect_one()) mbar_arrive(sb + G_RDY + k * 8);
                    }
                }
            } else if (phases & 1) {
#pragma unroll 1
                for (int q = wid - 10; q < 39; q += 2) {
                    mbar_wait(sb + G_PUB + q * 8, 0);
                    fence_gpu();
                    if (elect_one()) {
                        st_relaxed(g_FT + n * 32 + (q & 1), epoch * 32 + (q >> 1) + 1);
                        if (q == 6) GT(1, 2);
                        if (q == 7) GT(1, 3);
                    }
                }
            }
        }
        cluster_sync();
    }
}

}

extern "C" void kernel_launch(void* const* d_in, const int* in_sizes, int n_in, void* d_out, int out_size) {
    typedef const __nv_bfloat16* bp;
    __nv_bfloat16* out = (__nv_bfloat16*)d_out;
    const SsmArgs ssm = {(bp)d_in[1], (bp)d_in[2], (bp)d_in[3], (bp)d_in[4], (bp)d_in[5], (bp)d_in[6]};
    const bp x = (bp)d_in[7], mem0 = (bp)d_in[8];
    static int nsm = 0;
    typedef CUresult (*EncodeFn)(CUtensorMap*, CUtensorMapDataType, cuuint32_t, void*, const cuuint64_t*, const cuuint64_t*, const cuuint32_t*,
                                 const cuuint32_t*, CUtensorMapInterleave, CUtensorMapSwizzle, CUtensorMapL2promotion, CUtensorMapFloatOOBfill);
    static EncodeFn encode = nullptr;
    if (!nsm) {
        cudaFuncSetAttribute(k_rec, cudaFuncAttributeMaxDynamicSharedMemorySize, R_SMEM);
        cudaFuncSetAttribute(k_rec, cudaFuncAttributeNonPortableClusterSizeAllowed, 1);
        cudaFuncSetAttribute(k_bulk, cudaFuncAttributeMaxDynamicSharedMemorySize, G_SMEM);
        int dev = 0; cudaGetDevice(&dev);
        cudaDeviceGetAttribute(&nsm, cudaDevAttrMultiProcessorCount, dev);
        cudaDriverEntryPointQueryResult qr;
        cudaGetDriverEntryPoint("cuTensorMapEncodeTiled", (void**)&encode, cudaEnableDefault, &qr);
    }
    auto make_map = [&](const void* p, int rank, cuuint64_t d0, cuuint64_t d1, cuuint64_t d2, cuuint64_t s1, cuuint64_t s2,
                        cuuint32_t b0, cuuint32_t b1, cuuint32_t b2, CUtensorMapSwizzle sw) {
        CUtensorMap m;
        const cuuint64_t dims[3] = {d0, d1, d2}, strides[2] = {s1, s2};
        const cuuint32_t box[3] = {b0, b1, b2}, es[3] = {1, 1, 1};
        encode(&m, CU_TENSOR_MAP_DATA_TYPE_BFLOAT16, rank, (void*)p, dims, strides, box, es, CU_TENSOR_MAP_INTERLEAVE_NONE,
               sw, CU_TENSOR_MAP_L2_PROMOTION_L2_128B, CU_TENSOR_MAP_FLOAT_OOB_FILL_NONE);
        return m;
    };
    const CUtensorMap mapX = make_map(x, 2, D, S, 1, D * 2, 0, 32, 32, 1, CU_TENSOR_MAP_SWIZZLE_64B);
    const CUtensorMap mapXs = make_map(x, 2, D, S, 1, D * 2, 0, 120, 32, 1, CU_TENSOR_MAP_SWIZZLE_NONE);
    const CUtensorMap mapU = make_map(d_in[0], 2, D, S, 1, D * 2, 0, 8, 256, 1, CU_TENSOR_MAP_SWIZZLE_NONE);
    const CUtensorMap mapY = make_map(out, 2, OUTW, S, 1, OUTW * 2, 0, 8, 128, 1, CU_TENSOR_MAP_SWIZZLE_NONE);
    const CUtensorMap mapQ = make_map(d_in[9], 2, 4096, D, 1, 8192, 0, 64, 224, 1, CU_TENSOR_MAP_SWIZZLE_128B);
    const CUtensorMap mapK = make_map(d_in[10], 2, 4096, D, 1, 8192, 0, 32, 32, 1, CU_TENSOR_MAP_SWIZZLE_64B);
    const CUtensorMap mapV = make_map(d_in[11], 2, 4096, D, 1, 8192, 0, 32, 32, 1, CU_TENSOR_MAP_SWIZZLE_64B);
    const CUtensorMap mapO = make_map(d_in[12], 3, 32, 4096, 14, D * 2, 64, 32, 64, 7, CU_TENSOR_MAP_SWIZZLE_64B);
    const int nbulk = (nsm - 64) & ~1;
    k_rec<<<64, 384, R_SMEM, cudaStreamPerThread>>>(mapXs, mapU, mapY, ssm, (const uint8_t*)x, mem0, (const uint8_t*)d_in[10],
                                                    (const uint8_t*)d_in[11], (unsigned)(64 + nbulk), 0u);
    cudaLaunchAttribute pdl[1];
    pdl[0].id = cudaLaunchAttributeProgrammaticStreamSerialization;
    pdl[0].val.programmaticStreamSerializationAllowed = 1;
    cudaLaunchConfig_t cfg = {};
    cfg.stream = cudaStreamPerThread;
    cfg.attrs = pdl; cfg.numAttrs = 1;
    cfg.gridDim = dim3(nbulk); cfg.blockDim = dim3(384); cfg.dynamicSmemBytes = G_SMEM;
    cudaLaunchKernelEx(&cfg, k_bulk, mapX, mapK, mapV, mapQ, mapO, out, (unsigned)(64 + nbulk), 3);
}
```

```cpp
#include <cuda.h>
#include <cuda_runtime.h>
#include <cuda_bf16.h>
#include <cuda_fp16.h>
#include <stdint.h>
#include <string.h>

namespace {

constexpr int D = 448, S = 2048, NSEG = 64, DH = 256, NST = 256, OUTW = 896;
constexpr int RS = 16;

__device__ uint4 g_F[2 * 16 * 4 * 28 * 7 * 32];
__device__ __align__(128) uint8_t g_K[RS * 16 * 4 * 4 * 1792];
__device__ __align__(128) uint8_t g_V[RS * 16 * 56 * 512];
__device__ __align__(128) uint32_t g_P[RS * 16 * 14 * 32];
__device__ __align__(128) uint32_t g_U[RS * 16 * 56 * 32];
__device__ __align__(128) uint8_t g_ACC[98304];
__device__ unsigned g_FT[64 * 32];
__device__ unsigned g_CNT[NSEG * 32];
__device__ unsigned g_WD[32 * 32];
__device__ unsigned g_INIT, g_EXIT;
#define GT(k, i) {}

__host__ __device__ constexpr int sig0(int k) { return k == 6 ? 12 : 4 * (k >> 1) + (k & 1); }
__host__ __device__ constexpr int sig1(int k) { return k == 6 ? 13 : 4 * (k >> 1) + (k & 1) + 2; }
constexpr int SPIN = 1 << 22;

__device__ __forceinline__ uint32_t smem_u32(const void* p) { return (uint32_t)__cvta_generic_to_shared(p); }
__device__ __forceinline__ void mma16816(float* c, uint32_t a0, uint32_t a1, uint32_t a2, uint32_t a3, uint32_t b0, uint32_t b1) {
    asm volatile("mma.sync.aligned.m16n8k16.row.col.f32.bf16.bf16.f32 {%0,%1,%2,%3},{%4,%5,%6,%7},{%8,%9},{%0,%1,%2,%3};"
                 : "+f"(c[0]), "+f"(c[1]), "+f"(c[2]), "+f"(c[3]) : "r"(a0), "r"(a1), "r"(a2), "r"(a3), "r"(b0), "r"(b1));
}
__device__ __forceinline__ void mma16816z(float* c, uint32_t a0, uint32_t a1, uint32_t a2, uint32_t a3, uint32_t b0, uint32_t b1) {
    asm volatile("mma.sync.aligned.m16n8k16.row.col.f32.bf16.bf16.f32 {%0,%1,%2,%3},{%4,%5,%6,%7},{%8,%9},{%10,%10,%10,%10};"
                 : "=f"(c[0]), "=f"(c[1]), "=f"(c[2]), "=f"(c[3]) : "r"(a0), "r"(a1), "r"(a2), "r"(a3), "r"(b0), "r"(b1), "f"(0.f));
}
__device__ __forceinline__ void mma1688(float* c, uint32_t a0, uint32_t a1, uint32_t b0) {
    asm volatile("mma.sync.aligned.m16n8k8.row.col.f32.bf16.bf16.f32 {%0,%1,%2,%3},{%4,%5},{%6},{%0,%1,%2,%3};"
                 : "+f"(c[0]), "+f"(c[1]), "+f"(c[2]), "+f"(c[3]) : "r"(a0), "r"(a1), "r"(b0));
}
__device__ __forceinline__ void mmaq(float* c, const uint4& a, uint32_t b0, uint32_t b1) { mma16816(c, a.x, a.y, a.z, a.w, b0, b1); }
__device__ __forceinline__ void mmaqz(float* c, const uint4& a, uint32_t b0, uint32_t b1) { mma16816z(c, a.x, a.y, a.z, a.w, b0, b1); }
__device__ __forceinline__ uint32_t pack_bf16(float lo, float hi) {
    uint32_t r; asm("cvt.rn.bf16x2.f32 %0,%1,%2;" : "=r"(r) : "f"(hi), "f"(lo)); return r;
}
__device__ __forceinline__ uint32_t pack_bf16_again(float lo, float hi) {
    uint32_t r; asm("cvt.rn.relu.bf16x2.f32 %0,%1,%2;" : "=r"(r) : "f"(hi), "f"(lo)); return r;
}
__device__ __forceinline__ uint32_t pack_f16(float lo, float hi) {
    uint32_t r; asm("cvt.rn.f16x2.f32 %0,%1,%2;" : "=r"(r) : "f"(hi), "f"(lo)); return r;
}
__device__ __forceinline__ uint32_t prmt(uint32_t a, uint32_t b, uint32_t sel) { uint32_t r; asm("prmt.b32 %0,%1,%2,%3;" : "=r"(r) : "r"(a), "r"(b), "r"(sel)); return r; }
__device__ __forceinline__ uint32_t movm(uint32_t a) {
    uint32_t d; asm volatile("movmatrix.sync.aligned.m8n8.trans.b16 %0,%1;" : "=r"(d) : "r"(a)); return d;
}
__device__ __forceinline__ void ldsm4(uint32_t* r, uint32_t a) {
    asm volatile("ldmatrix.sync.aligned.m8n8.x4.shared.b16 {%0,%1,%2,%3},[%4];" : "=r"(r[0]), "=r"(r[1]), "=r"(r[2]), "=r"(r[3]) : "r"(a) : "memory");
}
__device__ __forceinline__ uint4 ldsm4q(uint32_t a) { uint32_t r[4]; ldsm4(r, a); return make_uint4(r[0], r[1], r[2], r[3]); }
__device__ __forceinline__ void stsm4(uint32_t a, const uint4& v) {
    asm volatile("stmatrix.sync.aligned.m8n8.x4.shared.b16 [%0],{%1,%2,%3,%4};" ::"r"(a), "r"(v.x), "r"(v.y), "r"(v.z), "r"(v.w) : "memory");
}
__device__ __forceinline__ void stsm4t(uint32_t a, const uint4& v) {
    asm volatile("stmatrix.sync.aligned.m8n8.x4.trans.shared.b16 [%0],{%1,%2,%3,%4};" ::"r"(a), "r"(v.x), "r"(v.y), "r"(v.z), "r"(v.w) : "memory");
}
__device__ __forceinline__ uint4 movm4(const uint4& v) { return make_uint4(movm(v.x), movm(v.y), movm(v.z), movm(v.w)); }
__device__ __forceinline__ void stsm2(uint32_t a, uint32_t x, uint32_t y) {
    asm volatile("stmatrix.sync.aligned.m8n8.x2.shared.b16 [%0],{%1,%2};" ::"r"(a), "r"(x), "r"(y) : "memory");
}
__device__ __forceinline__ uint4 lds128(uint32_t a) {
    uint4 v; asm volatile("ld.shared.v4.u32 {%0,%1,%2,%3},[%4];" : "=r"(v.x), "=r"(v.y), "=r"(v.z), "=r"(v.w) : "r"(a) : "memory"); return v;
}
__device__ __forceinline__ float4 lds128f(uint32_t a) {
    float4 v; asm volatile("ld.shared.v4.f32 {%0,%1,%2,%3},[%4];" : "=f"(v.x), "=f"(v.y), "=f"(v.z), "=f"(v.w) : "r"(a) : "memory"); return v;
}
__device__ __forceinline__ uint2 lds64(uint32_t a) {
    uint2 v; asm volatile("ld.shared.v2.u32 {%0,%1},[%2];" : "=r"(v.x), "=r"(v.y) : "r"(a) : "memory"); return v;
}
__device__ __forceinline__ float2 lds64f(uint32_t a) {
    float2 v; asm volatile("ld.shared.v2.f32 {%0,%1},[%2];" : "=f"(v.x), "=f"(v.y) : "r"(a) : "memory"); return v;
}
__device__ __forceinline__ uint32_t lds32(uint32_t a) {
    uint32_t v; asm volatile("ld.shared.u32 %0,[%1];" : "=r"(v) : "r"(a) : "memory"); return v;
}
__device__ __forceinline__ uint32_t lds32v(uint32_t a) {
    uint32_t v; asm volatile("ld.volatile.shared.u32 %0,[%1];" : "=r"(v) : "r"(a) : "memory"); return v;
}
__device__ __forceinline__ float lds32f(uint32_t a) { return __uint_as_float(lds32(a)); }
__device__ __forceinline__ void sts128(uint32_t a, uint32_t x, uint32_t y, uint32_t z, uint32_t w) {
    asm volatile("st.shared.v4.u32 [%0],{%1,%2,%3,%4};" ::"r"(a), "r"(x), "r"(y), "r"(z), "r"(w) : "memory");
}
__device__ __forceinline__ void sts64(uint32_t a, uint32_t x, uint32_t y) {
    asm volatile("st.shared.v2.u32 [%0],{%1,%2};" ::"r"(a), "r"(x), "r"(y) : "memory");
}
__device__ __forceinline__ void sts64f(uint32_t a, float x, float y) { sts64(a, __float_as_uint(x), __float_as_uint(y)); }
__device__ __forceinline__ void sts32(uint32_t a, uint32_t x) { asm volatile("st.shared.u32 [%0],%1;" ::"r"(a), "r"(x) : "memory"); }
__device__ __forceinline__ void sts32f(uint32_t a, float x) { sts32(a, __float_as_uint(x)); }
#define ADDR3(ins) "{.reg .u32 t; add.u32 t," ins "}"
template <int I> __device__ __forceinline__ uint4 lds128u(uint32_t a, uint32_t u) {
    uint4 v; asm volatile(ADDR3("%4,%5; ld.shared.v4.u32 {%0,%1,%2,%3},[t+%6];") : "=r"(v.x), "=r"(v.y), "=r"(v.z), "=r"(v.w) : "r"(a), "r"(u), "n"(I) : "memory"); return v;
}
template <int I> __device__ __forceinline__ float4 lds128fu(uint32_t a, uint32_t u) {
    const uint4 v = lds128u<I>(a, u); return make_float4(__uint_as_float(v.x), __uint_as_float(v.y), __uint_as_float(v.z), __uint_as_float(v.w));
}
template <int I> __device__ __forceinline__ uint2 lds64u(uint32_t a, uint32_t u) {
    uint2 v; asm volatile(ADDR3("%2,%3; ld.shared.v2.u32 {%0,%1},[t+%4];") : "=r"(v.x), "=r"(v.y) : "r"(a), "r"(u), "n"(I) : "memory"); return v;
}
template <int I> __device__ __forceinline__ float2 lds64fu(uint32_t a, uint32_t u) { const uint2 v = lds64u<I>(a, u); return make_float2(__uint_as_float(v.x), __uint_as_float(v.y)); }
template <int I> __device__ __forceinline__ uint4 ldsm4u(uint32_t a, uint32_t u) {
    uint4 v; asm volatile(ADDR3("%4,%5; ldmatrix.sync.aligned.m8n8.x4.shared.b16 {%0,%1,%2,%3},[t+%6];") : "=r"(v.x), "=r"(v.y), "=r"(v.z), "=r"(v.w) : "r"(a), "r"(u), "n"(I) : "memory"); return v;
}
template <int I> __device__ __forceinline__ uint2 ldsm2u(uint32_t a, uint32_t u) {
    uint2 v; asm volatile(ADDR3("%2,%3; ldmatrix.sync.aligned.m8n8.x2.shared.b16 {%0,%1},[t+%4];") : "=r"(v.x), "=r"(v.y) : "r"(a), "r"(u), "n"(I) : "memory"); return v;
}
template <int I> __device__ __forceinline__ void stsm4u(uint32_t a, uint32_t u, uint32_t x, uint32_t y, uint32_t z, uint32_t w) {
    asm volatile(ADDR3("%0,%1; stmatrix.sync.aligned.m8n8.x4.shared.b16 [t+%2],{%3,%4,%5,%6};") ::"r"(a), "r"(u), "n"(I), "r"(x), "r"(y), "r"(z), "r"(w) : "memory");
}
template <int I> __device__ __forceinline__ void stsm2u(uint32_t a, uint32_t u, uint32_t x, uint32_t y) {
    asm volatile(ADDR3("%0,%1; stmatrix.sync.aligned.m8n8.x2.shared.b16 [t+%2],{%3,%4};") ::"r"(a), "r"(u), "n"(I), "r"(x), "r"(y) : "memory");
}
template <int I> __device__ __forceinline__ uint4 ldsm4tu(uint32_t a, uint32_t u) {
    uint4 v; asm volatile(ADDR3("%4,%5; ldmatrix.sync.aligned.m8n8.x4.trans.shared.b16 {%0,%1,%2,%3},[t+%6];") : "=r"(v.x), "=r"(v.y), "=r"(v.z), "=r"(v.w) : "r"(a), "r"(u), "n"(I) : "memory"); return v;
}
__device__ __forceinline__ uint32_t uni(uint32_t v) { return __shfl_sync(0xffffffffu, v, 0); }
template <int I> __device__ __forceinline__ void sts128u(uint32_t a, uint32_t u, uint32_t x, uint32_t y, uint32_t z, uint32_t w) {
    asm volatile(ADDR3("%0,%1; st.shared.v4.u32 [t+%2],{%3,%4,%5,%6};") ::"r"(a), "r"(u), "n"(I), "r"(x), "r"(y), "r"(z), "r"(w) : "memory");
}
template <int I> __device__ __forceinline__ void sts64u(uint32_t a, uint32_t u, uint32_t x, uint32_t y) {
    asm volatile(ADDR3("%0,%1; st.shared.v2.u32 [t+%2],{%3,%4};") ::"r"(a), "r"(u), "n"(I), "r"(x), "r"(y) : "memory");
}
__device__ __forceinline__ uint32_t add_here(uint32_t a, uint32_t b) { uint32_t r; asm volatile("add.u32 %0,%1,%2;" : "=r"(r) : "r"(a), "r"(b)); return r; }
__device__ __forceinline__ uint8_t* add_here(uint8_t* p, uint32_t o) { uint8_t* r; asm volatile("{.reg .u64 t; cvt.u64.u32 t,%2; add.u64 %0,%1,t;}" : "=l"(r) : "l"(p), "r"(o)); return r; }
__device__ __forceinline__ uint32_t mapa(uint32_t a, uint32_t r) {
    uint32_t o; asm("mapa.shared::cluster.u32 %0,%1,%2;" : "=r"(o) : "r"(a), "r"(r)); return o;
}
__device__ __forceinline__ void st_async4(uint32_t dst, uint32_t bar, float x, float y, float z, float w) {
    asm volatile("st.async.weak.shared::cluster.mbarrier::complete_tx::bytes.v4.f32 [%0],{%1,%2,%3,%4},[%5];"
                 ::"r"(dst), "f"(x), "f"(y), "f"(z), "f"(w), "r"(bar) : "memory");
}
__device__ __forceinline__ void st_async2(uint32_t dst, uint32_t bar, float x, float y) {
    asm volatile("st.async.weak.shared::cluster.mbarrier::complete_tx::bytes.v2.f32 [%0],{%1,%2},[%3];"
                 ::"r"(dst), "f"(x), "f"(y), "r"(bar) : "memory");
}
__device__ __forceinline__ void st_async2_if(bool on, uint32_t dst, uint32_t bar, float x, float y) {
    asm volatile("{.reg .pred p; setp.ne.b32 p,%4,0; @p st.async.weak.shared::cluster.mbarrier::complete_tx::bytes.v2.f32 [%0],{%1,%2},[%3];}"
                 ::"r"(dst), "f"(x), "f"(y), "r"(bar), "r"((int)on) : "memory");
}
__device__ __forceinline__ void st_async1_if(bool on, uint32_t dst, uint32_t bar, uint32_t x) {
    asm volatile("{.reg .pred p; setp.ne.b32 p,%3,0; @p st.async.weak.shared::cluster.mbarrier::complete_tx::bytes.u32 [%0],%1,[%2];}"
                 ::"r"(dst), "r"(x), "r"(bar), "r"((int)on) : "memory");
}
__device__ __forceinline__ float ldr32f(uint32_t a) {
    float v; asm volatile("ld.shared::cluster.f32 %0,[%1];" : "=f"(v) : "r"(a) : "memory"); return v;
}
__device__ __forceinline__ void mbar_init(uint32_t bar, int cnt) { asm volatile("mbarrier.init.shared::cta.b64 [%0],%1;" ::"r"(bar), "r"(cnt) : "memory"); }
__device__ __forceinline__ void mbar_expect(uint32_t bar, int bytes) {
    asm volatile("mbarrier.arrive.expect_tx.shared::cta.b64 _,[%0],%1;" ::"r"(bar), "r"(bytes) : "memory");
}
__device__ __forceinline__ void mbar_arrive(uint32_t a) { asm volatile("mbarrier.arrive.release.cta.shared::cta.b64 _,[%0];" ::"r"(a) : "memory"); }
__device__ __forceinline__ void mbar_wait(uint32_t bar, uint32_t parity) {
    asm volatile("{.reg .pred p; .reg .u32 n; mov.u32 n,0;\n"
                 "W: mbarrier.try_wait.parity.shared::cta.b64 p,[%0],%1; @p bra D; add.u32 n,n,1; setp.lt.u32 p,n,%2; @p bra W; trap;\n"
                 "D:}" ::"r"(bar), "r"(parity), "n"(SPIN) : "memory");
}
__device__ __forceinline__ void mbar_wait_cl(uint32_t bar) {
    asm volatile("{.reg .pred p,q; .reg .u32 n; mov.u32 n,0;\n"
                 "W: add.u32 n,n,1; setp.gt.u32 q,n,%1; @q trap; mbarrier.try_wait.parity.relaxed.cluster.shared::cta.b64 p,[%0],0; @!p bra W;\n"
                 "fence.acquire.sync_restrict::shared::cluster.cluster;}" ::"r"(bar), "n"(SPIN) : "memory");
}
__device__ __forceinline__ void bulk_g2s(uint32_t dst, const void* src, int bytes, uint32_t bar) {
    asm volatile("cp.async.bulk.shared::cluster.global.mbarrier::complete_tx::bytes [%0],[%1],%2,[%3];"
                 ::"r"(dst), "l"(src), "r"(bytes), "r"(bar) : "memory");
}
__device__ __forceinline__ void tma2d(uint32_t dst, const CUtensorMap* map, int x, int y, uint32_t bar) {
    asm volatile("cp.async.bulk.tensor.2d.shared::cluster.global.mbarrier::complete_tx::bytes [%0],[%1,{%2,%3}],[%4];"
                 ::"r"(dst), "l"(map), "r"(x), "r"(y), "r"(bar) : "memory");
}
__device__ __forceinline__ void tma2d_pair(uint32_t dst, const CUtensorMap* map, int x, int y, uint32_t bar) {
    asm volatile("cp.async.bulk.tensor.2d.shared::cluster.global.mbarrier::complete_tx::bytes.multicast::cluster [%0],[%1,{%2,%3}],[%4],%5;"
                 ::"r"(dst), "l"(map), "r"(x), "r"(y), "r"(bar), "h"((uint16_t)3) : "memory");
}
__device__ __forceinline__ void tma3d(uint32_t dst, const CUtensorMap* map, int x, int y, int z, uint32_t bar) {
    asm volatile("cp.async.bulk.tensor.3d.shared::cluster.global.mbarrier::complete_tx::bytes [%0],[%1,{%2,%3,%4}],[%5];"
                 ::"r"(dst), "l"(map), "r"(x), "r"(y), "r"(z), "r"(bar) : "memory");
}
__device__ __forceinline__ void prefetch_l2(const void* p, int bytes) {
    asm volatile("cp.async.bulk.prefetch.L2.global [%0],%1;" ::"l"(p), "r"(bytes) : "memory");
}
__device__ __forceinline__ int fresh_lane() { int l; asm volatile("mov.u32 %0,%%laneid;" : "=r"(l)); return __shfl_sync(0xffffffffu, l, l); }
__device__ __forceinline__ bool elect_one() {
    uint32_t r; asm volatile("{.reg .pred p; elect.sync _|p,0xffffffff; selp.u32 %0,1,0,p;}" : "=r"(r)); return r;
}
__device__ __forceinline__ void bar_sync(int id, int n) { asm volatile("bar.sync %0,%1;" ::"r"(id), "r"(n) : "memory"); }
__device__ __forceinline__ void bar_arrive(int id, int n) { asm volatile("bar.arrive %0,%1;" ::"r"(id), "r"(n) : "memory"); }
__device__ __forceinline__ uint4 ld_relaxed4(const void* p) {
    uint4 v; asm volatile("ld.relaxed.gpu.global.v4.u32 {%0,%1,%2,%3},[%4];" : "=r"(v.x), "=r"(v.y), "=r"(v.z), "=r"(v.w) : "l"(p) : "memory"); return v;
}
__device__ __forceinline__ unsigned ld_relaxed(const unsigned* p) {
    unsigned v; asm volatile("ld.relaxed.gpu.global.u32 %0,[%1];" : "=r"(v) : "l"(p) : "memory"); return v;
}
__device__ __forceinline__ void st_relaxed(unsigned* p, unsigned v) { asm volatile("st.relaxed.gpu.global.u32 [%0],%1;" ::"l"(p), "r"(v) : "memory"); }
__device__ __forceinline__ void stg32(void* p, uint32_t v) { asm volatile("st.global.u32 [%0],%1;" ::"l"(p), "r"(v) : "memory"); }
__device__ __forceinline__ void red_inc(unsigned* p) { asm volatile("red.relaxed.gpu.global.add.u32 [%0],1;" ::"l"(p) : "memory"); }
__device__ __forceinline__ void red_add(unsigned* p, unsigned v) { asm volatile("red.relaxed.gpu.global.add.u32 [%0],%1;" ::"l"(p), "r"(v) : "memory"); }
__device__ __forceinline__ void fence_acq() { asm volatile("fence.acquire.gpu;" ::: "memory"); }
__device__ __forceinline__ void fence_rel() { asm volatile("fence.release.gpu;" ::: "memory"); }
__device__ __forceinline__ void wait_count(const unsigned* p, unsigned goal, unsigned sleep_ns) {
    int it = 0;
    while ((int)(ld_relaxed(p) - goal) < 0) { if (sleep_ns) __nanosleep(sleep_ns); if (++it > SPIN) __trap(); }
}
__device__ __forceinline__ void wait_count_warp(const unsigned* p, unsigned goal, unsigned sleep_ns) {
    int it = 0;
    while (__any_sync(0xffffffffu, (int)(ld_relaxed(p) - goal) < 0)) { if (sleep_ns) __nanosleep(sleep_ns); if (++it > SPIN) __trap(); }
}
__device__ __forceinline__ void red_bf16x8(void* p, bool on, uint32_t x, uint32_t y, uint32_t z, uint32_t w) {
    asm volatile("{.reg .pred p; setp.ne.b32 p,%5,0; @p red.relaxed.gpu.global.add.noftz.v4.bf16x2 [%0],{%1,%2,%3,%4};}"
                 ::"l"(p), "r"(x), "r"(y), "r"(z), "r"(w), "r"((int)on) : "memory");
}
__device__ __forceinline__ void mbar_arrive_if(bool on, uint32_t a) {
    asm volatile("{.reg .pred p; setp.ne.b32 p,%1,0; @p mbarrier.arrive.release.cta.shared::cta.b64 _,[%0];}" ::"r"(a), "r"((int)on) : "memory");
}
__device__ __forceinline__ void mbar_arrive_cl_if(bool on, uint32_t a) {
    asm volatile("{.reg .pred p; setp.ne.b32 p,%1,0; @p mbarrier.arrive.relaxed.cluster.shared::cluster.b64 _,[%0];}" ::"r"(a), "r"((int)on) : "memory");
}
__device__ __forceinline__ uint32_t any_reg() { uint32_t r; asm volatile("" : "=r"(r)); return r; }
__device__ __forceinline__ float ex2(float x) { float y; asm("ex2.approx.ftz.f32 %0,%1;" : "=f"(y) : "f"(x)); return y; }
__device__ __forceinline__ float rcp(float x) { float y; asm("rcp.approx.ftz.f32 %0,%1;" : "=f"(y) : "f"(x)); return y; }
__device__ __forceinline__ uint32_t clk() {
    uint32_t c; asm volatile("{.reg .u64 t; .reg .u32 h; mov.u64 t,%%clock64; mov.b64 {%0,h},t;}" : "=r"(c)::"memory"); return c;
}
__device__ __forceinline__ uint32_t hadd_bf(uint32_t a, uint32_t b) { uint32_t r; asm("add.rn.bf16x2 %0,%1,%2;" : "=r"(r) : "r"(a), "r"(b)); return r; }
__device__ __forceinline__ uint32_t hmul_bf(uint32_t a, uint32_t b) { uint32_t r; asm("mul.rn.bf16x2 %0,%1,%2;" : "=r"(r) : "r"(a), "r"(b)); return r; }
__device__ __forceinline__ uint32_t hsum4(uint32_t a, uint32_t b, uint32_t c, uint32_t d) { return hadd_bf(hadd_bf(a, b), hadd_bf(c, d)); }
__device__ __forceinline__ uint32_t amax_bf(uint32_t a, uint32_t b) { uint32_t r; asm("max.xorsign.abs.bf16x2 %0,%1,%2;" : "=r"(r) : "r"(a), "r"(b)); return r; }
__device__ __forceinline__ float4 sum4(float4 a, float4 b, float4 c, float4 d) {
    return make_float4((a.x + b.x) + (c.x + d.x), (a.y + b.y) + (c.y + d.y), (a.z + b.z) + (c.z + d.z), (a.w + b.w) + (c.w + d.w));
}
__device__ __forceinline__ void cluster_arrive() { asm volatile("barrier.cluster.arrive.relaxed.aligned;" ::: "memory"); }
__device__ __forceinline__ void cluster_arrive_rel() { asm volatile("barrier.cluster.arrive.release.aligned;" ::: "memory"); }
__device__ __forceinline__ void cluster_wait() { asm volatile("barrier.cluster.wait.aligned;" ::: "memory"); }
#define SCHED_FENCE(z, k) do { if ((z) == (k)) __trap(); } while (0)

template <int TB>
__device__ __forceinline__ void wgmma224(float* d, uint64_t da, uint64_t db, int accumulate) {
    asm volatile("{.reg .pred p; setp.ne.b32 p,%114,0;\n"
                 "wgmma.mma_async.sync.aligned.m64n224k16.f32.bf16.bf16 {%0,%1,%2,%3,%4,%5,%6,%7,%8,%9,%10,%11,%12,%13,%14,%15,%16,%17,%18,%19,%20,%21,%22,%23,%24,%25,%26,%27,%28,%29,%30,%31,%32,%33,%34,%35,%36,%37,%38,%39,%40,%41,%42,%43,%44,%45,%46,%47,%48,%49,%50,%51,%52,%53,%54,%55,%56,%57,%58,%59,%60,%61,%62,%63,%64,%65,%66,%67,%68,%69,%70,%71,%72,%73,%74,%75,%76,%77,%78,%79,%80,%81,%82,%83,%84,%85,%86,%87,%88,%89,%90,%91,%92,%93,%94,%95,%96,%97,%98,%99,%100,%101,%102,%103,%104,%105,%106,%107,%108,%109,%110,%111},%112,%113,p,1,1,0,%115;}"
                 : "+f"(d[0]), "+f"(d[1]), "+f"(d[2]), "+f"(d[3]), "+f"(d[4]), "+f"(d[5]), "+f"(d[6]), "+f"(d[7]), "+f"(d[8]), "+f"(d[9]), "+f"(d[10]), "+f"(d[11]), "+f"(d[12]), "+f"(d[13]), "+f"(d[14]), "+f"(d[15]), "+f"(d[16]), "+f"(d[17]), "+f"(d[18]), "+f"(d[19]), "+f"(d[20]), "+f"(d[21]), "+f"(d[22]), "+f"(d[23]), "+f"(d[24]), "+f"(d[25]), "+f"(d[26]), "+f"(d[27]), "+f"(d[28]), "+f"(d[29]), "+f"(d[30]), "+f"(d[31]), "+f"(d[32]), "+f"(d[33]), "+f"(d[34]), "+f"(d[35]), "+f"(d[36]), "+f"(d[37]), "+f"(d[38]), "+f"(d[39]), "+f"(d[40]), "+f"(d[41]), "+f"(d[42]), "+f"(d[43]), "+f"(d[44]), "+f"(d[45]), "+f"(d[46]), "+f"(d[47]), "+f"(d[48]), "+f"(d[49]), "+f"(d[50]), "+f"(d[51]), "+f"(d[52]), "+f"(d[53]), "+f"(d[54]), "+f"(d[55]), "+f"(d[56]), "+f"(d[57]), "+f"(d[58]), "+f"(d[59]), "+f"(d[60]), "+f"(d[61]), "+f"(d[62]), "+f"(d[63]), "+f"(d[64]), "+f"(d[65]), "+f"(d[66]), "+f"(d[67]), "+f"(d[68]), "+f"(d[69]), "+f"(d[70]), "+f"(d[71]), "+f"(d[72]), "+f"(d[73]), "+f"(d[74]), "+f"(d[75]), "+f"(d[76]), "+f"(d[77]), "+f"(d[78]), "+f"(d[79]), "+f"(d[80]), "+f"(d[81]), "+f"(d[82]), "+f"(d[83]), "+f"(d[84]), "+f"(d[85]), "+f"(d[86]), "+f"(d[87]), "+f"(d[88]), "+f"(d[89]), "+f"(d[90]), "+f"(d[91]), "+f"(d[92]), "+f"(d[93]), "+f"(d[94]), "+f"(d[95]), "+f"(d[96]), "+f"(d[97]), "+f"(d[98]), "+f"(d[99]), "+f"(d[100]), "+f"(d[101]), "+f"(d[102]), "+f"(d[103]), "+f"(d[104]), "+f"(d[105]), "+f"(d[106]), "+f"(d[107]), "+f"(d[108]), "+f"(d[109]), "+f"(d[110]), "+f"(d[111])
                 : "l"(da), "l"(db), "r"(accumulate), "n"(TB));
}
__device__ __forceinline__ void wgmma64(float* d, uint64_t da, uint64_t db, int accumulate) {
    asm volatile("{.reg .pred p; setp.ne.b32 p,%34,0;\n"
                 "wgmma.mma_async.sync.aligned.m64n64k16.f32.bf16.bf16 {%0,%1,%2,%3,%4,%5,%6,%7,%8,%9,%10,%11,%12,%13,%14,%15,%16,%17,%18,%19,%20,%21,%22,%23,%24,%25,%26,%27,%28,%29,%30,%31},%32,%33,p,1,1,0,0;}"
                 : "+f"(d[0]), "+f"(d[1]), "+f"(d[2]), "+f"(d[3]), "+f"(d[4]), "+f"(d[5]), "+f"(d[6]), "+f"(d[7]), "+f"(d[8]), "+f"(d[9]), "+f"(d[10]), "+f"(d[11]), "+f"(d[12]), "+f"(d[13]), "+f"(d[14]), "+f"(d[15]), "+f"(d[16]), "+f"(d[17]), "+f"(d[18]), "+f"(d[19]), "+f"(d[20]), "+f"(d[21]), "+f"(d[22]), "+f"(d[23]), "+f"(d[24]), "+f"(d[25]), "+f"(d[26]), "+f"(d[27]), "+f"(d[28]), "+f"(d[29]), "+f"(d[30]), "+f"(d[31])
                 : "l"(da), "l"(db), "r"(accumulate));
}
__device__ __forceinline__ uint64_t sdesc(uint32_t addr, uint32_t lbo, uint32_t sbo, uint64_t swizzle) {
    return (uint64_t)((addr & 0x3FFFF) >> 4) | ((uint64_t)(lbo >> 4) << 16) | ((uint64_t)(sbo >> 4) << 32) | (swizzle << 62);
}
__device__ __forceinline__ void wg_fence() { asm volatile("wgmma.fence.sync.aligned;" ::: "memory"); }
__device__ __forceinline__ void wg_commit() { asm volatile("wgmma.commit_group.sync.aligned;" ::: "memory"); }
template <int N> __device__ __forceinline__ void wg_wait() { asm volatile("wgmma.wait_group.sync.aligned %0;" ::"n"(N) : "memory"); }
constexpr float LOG2E = 1.4426950408889634f;
constexpr uint32_t ONE2 = 0x3f803f80u;
constexpr uint32_t CNT16 = 0x41800000u;
constexpr uint32_t SAFE_LO = (127u - 40u) << 23, SAFE_SPAN = 80u << 23;

constexpr int C_IO = 0;
constexpr int C_UP = 2176, C_UW = 2 * C_UP + 16;
constexpr int C_U = C_IO + 32768;
constexpr int C_RN = 16, C_RX = 576, C_RM = 624, C_RF = C_RM + 4 * 64, C_RW = C_RF + 2 * 80;
constexpr int C_R = C_U + 8 * C_UW;
constexpr int C_TW = 56 * 144;
constexpr int C_T = C_R + 8 * C_RW * 4;
constexpr int C_END = C_T + 8 * C_TW;

struct SsmArgs { const __nv_bfloat16 *lar, *aim, *cre, *cim, *ldt, *dsk; };
struct cpx { float r, i; };
__device__ __forceinline__ cpx csq(cpx a) { return {fmaf(a.r, a.r, -a.i * a.i), (a.r + a.r) * a.i}; }
__device__ __forceinline__ cpx cexp(float er, float wi, float p) { const float e = ex2(er * p), x = wi * p; return {e * __cosf(x), e * __sinf(x)}; }
struct hfac { uint32_t v, s; };
__device__ __forceinline__ hfac hfactor(cpx a) { return {pack_f16(a.r, a.i), pack_f16(-a.i, a.r)}; }
__device__ __forceinline__ uint32_t hcmul(uint32_t a, hfac b) {
    uint32_t r;
    asm("{.reg .f16 l,h; .reg .b32 x,y; mov.b32 {l,h},%1; mov.b32 x,{l,l}; mov.b32 y,{h,h}; mul.rn.f16x2 x,x,%2; fma.rn.f16x2 %0,y,%3,x;}" : "=r"(r) : "r"(a), "r"(b.v), "r"(b.s));
    return r;
}
__device__ __forceinline__ void mmah(float* c, const uint4& a, uint32_t b0, uint32_t b1) {
    asm volatile("mma.sync.aligned.m16n8k16.row.col.f32.f16.f16.f32 {%0,%1,%2,%3},{%4,%5,%6,%7},{%8,%9},{%0,%1,%2,%3};"
                 : "+f"(c[0]), "+f"(c[1]), "+f"(c[2]), "+f"(c[3]) : "r"(a.x), "r"(a.y), "r"(a.z), "r"(a.w), "r"(b0), "r"(b1));
}

__device__ __forceinline__ void ssm_kernel_values(uint32_t tb, uint32_t rb, int d, int lane, const SsmArgs& p) {
    const int g = lane >> 2, t = lane & 3;
    const float dt = __bfloat162float(__float2bfloat16(expf(__bfloat162float(p.ldt[d]))));
    float up;
    {
        const uint4 a = __ldg((const uint4*)(p.lar + d * NST) + lane), b = __ldg((const uint4*)(p.aim + d * NST) + lane);
        const uint4 v = __ldg((const uint4*)(p.cre + d * NST) + lane), z = __ldg((const uint4*)(p.cim + d * NST) + lane);
        sts128(rb + lane * 16, a.x, a.y, a.z, a.w); sts128(rb + 512 + lane * 16, b.x, b.y, b.z, b.w);
        sts128(rb + 1024 + lane * 16, v.x, v.y, v.z, v.w); sts128(rb + 1536 + lane * 16, z.x, z.y, z.z, z.w);
        const uint32_t m = amax_bf(amax_bf(amax_bf(v.x, v.y), amax_bf(v.z, v.w)), amax_bf(amax_bf(z.x, z.y), amax_bf(z.z, z.w)));
        const int e = __reduce_max_sync(0xffffffffu, max(m & 0x7f800000u, (m << 16) & 0x7f800000u)) >> 23;
        up = __uint_as_float((uint32_t)min(267 - e, 253) << 23);
    }
    float acc[2][3][4];
#pragma unroll
    for (int i = 0; i < 24; i++) (&acc[0][0][0])[i] = 0.f;
    const uint32_t wa = tb + lane * 4;
    const uint32_t la_ = tb + (lane & 15) * 144 + (lane >> 4) * 16, lb_ = tb + (32 + (lane & 7)) * 144 + (lane >> 3) * 16;
    sts32(wa, 0x00003c00u); sts32(wa + 53 * 144, 0u); sts32(wa + 54 * 144, 0u); sts32(wa + 55 * 144, 0u);
    auto par = [&](int o) { uint32_t k; asm volatile("{.reg .u16 h; ld.shared.u16 h,[%1]; cvt.u32.u16 %0,h;}" : "=r"(k) : "r"(rb + lane * 2 + o) : "memory"); return k; };
    __syncwarp();
    uint32_t la = par(0), ai = par(512), cr = par(1024), ci = par(1536);
#pragma unroll 1
    for (int it = 1; it <= 8; it++) {
        __syncwarp();
        const float er = (-__bfloat162float(__float2bfloat16(expf(__uint_as_float(la << 16)))) * dt) * LOG2E;
        const float wi = __uint_as_float(ai << 16) * dt;
        uint32_t x[21], y[32];
        x[0] = pack_f16(__uint_as_float(cr << 16) * up, __uint_as_float(ci << 16) * -up);
        la = par(64 * it); ai = par(512 + 64 * it); cr = par(1024 + 64 * it); ci = par(1536 + 64 * it);
        const cpx c1 = cexp(er, wi, 1.f), w8 = cexp(er, wi, 8.f), w64 = cexp(er, wi, 64.f), c256 = cexp(er, wi, 256.f);
        const cpx w1 = {c1.r, -c1.i}, w2 = csq(w1), w16 = csq(w8), w256 = {c256.r, -c256.i}, w512 = csq(w256);
        const hfac h1 = hfactor(w1), h2 = hfactor(w2), h4 = hfactor(csq(w2)), h256 = hfactor(w256), h512 = hfactor(w512), h1024 = hfactor(csq(w512));
        const hfac f[4] = {hfactor(w16), hfactor(csq(w16)), hfactor(w64), hfactor(csq(w64))};
        x[1] = hcmul(x[0], h1); x[2] = hcmul(x[0], h2); x[3] = hcmul(x[1], h2);
#pragma unroll
        for (int k = 0; k < 4; k++) x[4 + k] = hcmul(x[k], h4);
#pragma unroll
        for (int k = 0; k < 4; k++) x[8 + k] = hcmul(x[2 * k], h256);
        x[12] = hcmul(x[0], h512); x[13] = hcmul(x[4], h512); x[14] = hcmul(x[8], h512); x[15] = hcmul(x[10], h512);
        x[16] = hcmul(x[0], h1024); x[17] = hcmul(x[8], h1024); x[18] = hcmul(x[12], h1024); x[19] = hcmul(x[14], h1024); x[20] = hcmul(x[16], h1024);
        y[0] = 0; y[1] = pack_f16(w8.r, w8.i);
#pragma unroll
        for (int k = 2; k < 32; k++) {
            const int l = k < 4 ? 0 : (k < 8 ? 1 : (k < 16 ? 2 : 3));
            y[k] = k == (2 << l) ? f[l].v : hcmul(y[k - (2 << l)], f[l]);
        }
#pragma unroll
        for (int k = 0; k < 21; k++) sts32(wa + (32 + k) * 144, x[k]);
#pragma unroll
        for (int k = 1; k < 32; k++) sts32(wa + k * 144, y[k]);
        __syncwarp();
#pragma unroll
        for (int kp = 0; kp < 2; kp++) {
            const uint4 b0 = ldsm4q(lb_ + kp * 64), b1 = ldsm4q(lb_ + 8 * 144 + kp * 64), b2 = ldsm4q(lb_ + 16 * 144 + kp * 64);
#pragma unroll
            for (int m = 0; m < 2; m++) {
                const uint4 a0 = ldsm4q(la_ + m * 16 * 144 + kp * 64), a1 = ldsm4q(la_ + m * 16 * 144 + kp * 64 + 32);
                mmah(acc[m][0], a0, b0.x, b0.y); mmah(acc[m][1], a0, b1.x, b1.y); mmah(acc[m][2], a0, b2.x, b2.y);
                mmah(acc[m][0], a1, b0.z, b0.w); mmah(acc[m][1], a1, b1.z, b1.w); mmah(acc[m][2], a1, b2.z, b2.w);
            }
        }
    }
    __syncwarp();
    const float down = __uint_as_float((254u << 23) - __float_as_uint(up)), dt2 = 2.f * dt;
    auto put16 = [&](int pos, float v) { asm volatile("st.shared.u16 [%0],%1;" ::"r"(tb + pos * 2), "h"(__bfloat16_as_ushort(__float2bfloat16(v * dt2 * down))) : "memory"); };
    auto get16 = [&](int pos) { uint32_t k; asm volatile("{.reg .u16 h; ld.shared.u16 h,[%1]; cvt.u32.u16 %0,h;}" : "=r"(k) : "r"(tb + pos * 2) : "memory"); return k; };
    const int o1 = t < 2 ? 256 + 4 * t : 256 * t, s1 = t < 2 ? 2 : 4;
#pragma unroll
    for (int m = 0; m < 2; m++)
#pragma unroll
        for (int e = 0; e < 4; e++) {
            const int b = 128 * m + 8 * g + 64 * (e >> 1);
            put16(b + 2 * t + (e & 1), acc[m][0][e]); put16(b + o1 + s1 * (e & 1), acc[m][1][e]);
            put16(b + 1024 + 512 * t + 256 * (e & 1), acc[m][2][e]);
        }
    __syncwarp();
    constexpr int NIL = 3064;
    uint32_t r[31];
    auto pos = [&](int j, int o) {
        const int y = lane + 32 * j - C_RN - o, z = lane - o, rz = (z + ((z >> 1) & 1)) & ~1;
        if (j == 0) return y < 0 ? NIL : y;
        if (j < 8) return y;
        if (j == 8) return y < 256 ? y : rz + 32 * j - C_RN;
        if (j < 16) return rz + 32 * j - C_RN;
        return y < 512 ? rz + 32 * j - C_RN : (y <= 514 ? 512 : NIL);
    };
#pragma unroll
    for (int j = 0; j < 17; j++) r[j] = get16(pos(j, 0)) | (get16(pos(j, 1)) << 16);
    const uint32_t k1024 = get16(1024);
    r[17] = (lane == 19 || lane == 20 ? k1024 : 0u) | (lane == 20 || lane == 21 ? k1024 << 16 : 0u);
#pragma unroll
    for (int j = 0; j < 8; j++) {
        const int q = lane + 32 * (j & 1) + 16, o = 4 * (j >> 1) + 4;
        r[18 + j] = get16(q >= 32 && q < 64 ? 16 * q + o : NIL) | (get16(q >= 33 && q < 65 ? 16 * q - 16 + o : NIL) << 16);
    }
#pragma unroll
    for (int j = 0; j < 5; j++) {
        const int i = lane + 32 * j, hi = i >= 80, q = i - 80 * hi + 48, o = 8 * hi + 8;
        r[26 + j] = get16(q >= 64 ? 16 * q + o : NIL) | (get16(q >= 65 ? 16 * q - 16 + o : NIL) << 16);
    }
    const uint32_t ro = rb + lane * 4;
#pragma unroll
    for (int j = 0; j < 17; j++) sts32(ro + j * 128, r[j]);
    sts32(ro + 17 * 128, 0u); sts32(ro + C_RX * 4, r[17]); sts32(rb + (C_RX + 32 + (lane & 15)) * 4, 0u);
#pragma unroll
    for (int j = 0; j < 13; j++) sts32(ro + C_RM * 4 + j * 128, r[18 + j]);
}

template <int E0, int NE, int NK>
__device__ __forceinline__ void ssm_grouped(float (&acc)[16][4], uint32_t ub, uint32_t ta, int off, int width, int lane, uint32_t zero) {
    const int g = lane >> 2, t = lane & 3, mi = lane >> 3;
    const bool sh = off >= 8;
    const uint32_t ua = ub + ((mi ^ sh) & 1) * C_UP + (8 + (lane & 7) + ((mi + sh) >> 1) - 1 - sh) * 16;
    uint32_t band[5];
#pragma unroll
    for (int i = 0; i < 5; i++) {
        const int z = g - 2 * t + 8 - 8 * i + (sh ? 24 : 16) - off;
        band[i] = ((unsigned)z < (unsigned)width ? 0x3f80u : 0u) | ((unsigned)(z - 1) < (unsigned)width ? 0x3f800000u : 0u);
    }
    const uint4 q0 = make_uint4(band[1], band[0], band[2], band[1] ^ zero), q1 = make_uint4(band[3], band[2] ^ zero, band[4], band[3] ^ zero);
    uint32_t tp[NE][2];
#pragma unroll
    for (int e = 0; e < NE; e++) { tp[e][0] = lds32(ta + (8 * e + 16) * 4); tp[e][1] = lds32v(ta + (8 * e + 8) * 4); }
#pragma unroll
    for (int k = 0; k < NK; k++) {
        float w0[4], w1[4];
        const uint4 u0 = ldsm4q(ua + k * 256), u1 = ldsm4q(ua + k * 256 + 128);
        mmaqz(w0, q0, u0.x, u0.y); mmaqz(w1, q0, u1.x, u1.y);
        mmaq(w0, q1, u0.z, u0.w); mmaq(w1, q1, u1.z, u1.w);
        const uint4 a = make_uint4(pack_bf16(w0[0], w0[1]), pack_bf16(w0[2], w0[3]), pack_bf16(w1[0], w1[1]), pack_bf16(w1[2], w1[3]));
#pragma unroll
        for (int e = 0; e < NE; e++) if (2 * k + E0 + e < 16) mmaq(acc[2 * k + E0 + e], a, tp[e][0], tp[e][1]);
    }
}

__device__ __forceinline__ void ssm_unit(uint32_t sb, uint32_t bar, uint32_t par, bool init, int d0, const SsmArgs& p, const CUtensorMap* mapU, int barid, uint32_t zero) {
    const int lane = fresh_lane(), ch = __shfl_sync(0xffffffffu, threadIdx.x >> 5, 0);
    const int g = lane >> 2, t = lane & 3, mi = lane >> 3;
    if (ch == 0 && elect_one()) {
        if (init) { mbar_init(bar, 1); asm volatile("fence.proxy.async.shared::cta;" ::: "memory"); }
        mbar_expect(bar, 32768);
#pragma unroll 1
        for (int i = 0; i < 8; i++) tma2d(sb + C_IO + i * 4096, mapU, d0, 256 * i, bar);
    }
    const uint32_t ub = sb + C_U + ch * C_UW, rb = sb + C_R + ch * C_RW * 4;
    if (lane < 16) sts128(ub + (lane >> 3) * C_UP + (lane & 7) * 16, 0u, 0u, 0u, 0u);
    const uint32_t dk = __bfloat16_as_ushort(p.dsk[d0 + ch]);
    ssm_kernel_values(sb + C_T + ch * C_TW, rb, d0 + ch, lane, p);
    if (ch == 0 && elect_one()) GT(0, 8);
    const uint32_t ioa = sb + C_IO + ch * 4096 + lane * 16, pla = sb + C_U + (lane & 7) * C_UW + (mi & 1) * C_UP + (8 + 16 * ch + (mi >> 1)) * 16;
    if (init) bar_sync(barid, 256);
    mbar_wait(bar, par);
#pragma unroll
    for (int i = 0; i < 8; i++) stsm4t(pla + i * 32, ldsm4q(ioa + i * 512));
    bar_sync(barid, 256);
    float acc[16][4];
    const uint32_t ua = ub + (mi & 1) * C_UP + (8 + 8 * (mi >> 1) + (lane & 7)) * 16, ra = rb + (C_RN + g - 2 * t) * 4;
    {
        const uint32_t dg = (g == 2 * t ? dk : 0u) | (g == 2 * t + 1 ? dk << 16 : 0u);
        const uint4 q = make_uint4(dg, dg & zero, dk & zero, dg ^ zero);
#pragma unroll
        for (int j = 0; j < 8; j++) { const uint4 b = ldsm4q(ua + j * 256); mmaqz(acc[2 * j], q, b.x, b.y); mmaqz(acc[2 * j + 1], q, b.z, b.w); }
    }
#pragma unroll 1
    for (int rho = 0; rho < 8; rho++) {
        uint32_t b[16][2];
#pragma unroll
        for (int j = 0; j < 8; j++) { const uint4 v = ldsm4q(ua + j * 256 - rho * 16); b[2 * j][0] = v.x; b[2 * j][1] = v.y; b[2 * j + 1][0] = v.z; b[2 * j + 1][1] = v.w; }
        auto diag = [&](uint32_t a, int i) {
            const uint4 q = make_uint4(lds32(a), lds32(a + 32), lds32(a - 32), lds32v(a));
#pragma unroll
            for (int j = i; j < 16; j++) mmaq(acc[j], q, b[j - i][0], b[j - i][1]);
        };
#pragma unroll
        for (int i = 0; i < 4; i++) diag(ra + rho * 64 + i * 512, i);
        if (rho < 2) { diag(ra + rho * 64 + 2048, 4); diag(ra + rho * 64 + C_RX * 4, 8); }
    }
    const uint32_t ta = rb + (g - 2 * t) * 4;
#pragma unroll 1
    for (int ph = 0; ph < 4; ph++) ssm_grouped<4, 6, 6>(acc, ub, ta + (C_RM + 64 * ph) * 4, 4 * ph + 3 - (ph & 1), 3 + 2 * (ph & 1), lane, zero);
#pragma unroll 1
    for (int ph = 0; ph < 2; ph++) ssm_grouped<8, 8, 4>(acc, ub, ta + (C_RF + 80 * ph) * 4, 5 + 7 * ph, 7 + 2 * ph, lane, zero);
    if (ch == 0 && elect_one()) GT(0, 9);
    __syncwarp();
#pragma unroll
    for (int j = 0; j < 8; j++)
        stsm4t(ua + j * 256, make_uint4(pack_bf16(acc[2 * j][0], acc[2 * j][1]), pack_bf16(acc[2 * j][2], acc[2 * j][3]),
                                        pack_bf16(acc[2 * j + 1][0], acc[2 * j + 1][1]), pack_bf16(acc[2 * j + 1][2], acc[2 * j + 1][3])));
    bar_sync(barid, 256);
#pragma unroll
    for (int i = 0; i < 8; i++) stsm4t(ioa + i * 512, ldsm4q(pla + i * 32));
    asm volatile("fence.proxy.async.shared::cta;" ::: "memory");
}
__device__ __forceinline__ void ssm_store(uint32_t sb, int d0, int i, const CUtensorMap* mapY) {
    asm volatile("cp.async.bulk.tensor.2d.global.shared::cta.bulk_group [%0,{%1,%2}],[%3];" ::"l"(mapY), "r"(d0), "r"(128 * i), "r"(sb + C_IO + i * 2048) : "memory");
    asm volatile("cp.async.bulk.commit_group;" ::: "memory");
}

#define TRIG_DELAY 0
#define UW0 4
#define PF2 0
#define CLUSTER 4
#define UPIN 2
#define USTAG 1
#define SPLITMB 0
#define EXP_MIN 0
#define URES 3
#define GO_DEP 8
#define POLL_DELAY 400
constexpr int S_X = 0, S_V = 8192, S_KO = 15360, S_KS = 22528, S_TB = 29696, S_ONE = 36864, STGB = 37888;
constexpr int R_STG = C_U;
constexpr int R_WB = R_STG + 3 * STGB, WB = 7680;
constexpr int W_W0 = 0;
constexpr int W_MB = 3584, W_SMI = 5632;
constexpr int W_UP = 3584, W_QRT = 5376;
constexpr int W_TAB = 4 * WB + 5632;
constexpr int R_SMM = R_WB + 8 * WB;
constexpr int R_LS = R_SMM + 4096;
constexpr int R_ALIAS_END = R_LS + 10240;
constexpr int R_MISC = (R_ALIAS_END > C_END ? R_ALIAS_END : C_END);
constexpr int R_BAR = R_MISC + 16;
constexpr int B_KV = 0, B_SM = 512, B_LS = 1024, B_H = 1536, B_PUB = 2048, B_Z = 2560;
constexpr int R_SMEM = R_BAR + 3072;
static_assert(R_SMEM <= 232448, "smem");
enum { BR_TT = 0, BR_MB = 1, BR_SM = 2, BR_UP = 3, BR_RED = 4, BR_PRO = 5, BR_ALL = 6, BR_H = 7, BR_POLL = 8, BR_GO = 12 };

#define DBG(i)

__device__ __forceinline__ uint32_t acc_off(int c, int q, int lane) {
    return (lane & 7) * 16 + ((lane >> 3) & 1) * 256 + (lane >> 4) * 1024 + (q & 1) * 2048 + (q >> 1) * 16384 + c * 4096;
}
__device__ __forceinline__ int tile_of(int q, int i) { return i == 3 ? 3 + 8 * (q >> 1) : (q == 3 && i == 2 ? 7 : 4 * q + i); }
__device__ __forceinline__ uint32_t acc_slot(int s) { return (s & 1) * 128 + (s & 2) * 256 + (s & 4) * 8192; }

__global__ void __cluster_dims__(CLUSTER, 1, 1) __launch_bounds__(384, 1)
k_rec(const __grid_constant__ CUtensorMap mapXs, const __grid_constant__ CUtensorMap mapU, const __grid_constant__ CUtensorMap mapY, const SsmArgs ssm, const uint8_t* x, const __nv_bfloat16* __restrict__ mem0,
      const uint8_t* wk, const uint8_t* wv, unsigned ntotal, const uint32_t zero) {
    extern __shared__ __align__(1024) uint8_t smem[];
    const uint32_t sb = smem_u32(smem);
    const int tid = threadIdx.x, wid = __shfl_sync(0xffffffffu, tid >> 5, 0), w = wid & 3;
    const int h = blockIdx.x >> 2, c = blockIdx.x & 3;
    const int rk = blockIdx.x & (CLUSTER - 4);
    uint8_t* const accb = (uint8_t*)(((uintptr_t)g_ACC + 32767) & ~(uintptr_t)32767);

    asm volatile("griddepcontrol.launch_dependents;" ::: "memory");
    if (wid == 0 && elect_one()) GT(0, 0);

    if (wid < 8) {
        asm volatile("setmaxnreg.inc.sync.aligned.u32 232;");
        cluster_arrive();
        if (blockIdx.x < D / 8) ssm_unit(sb, sb + R_MISC + 8, 0, true, blockIdx.x * 8, ssm, &mapU, BR_PRO, zero);
        asm volatile("fence.proxy.async.shared::cta;" ::: "memory");
        if (wid == 0 && elect_one()) GT(0, 1);
        bar_sync(BR_ALL, 288);
        auto load_weights = [&](uint4 (&wr)[7][6], int lane) {
            wait_count_warp(g_FT + ((wid >> 2) * 32 + 2 * h + (c >> 1)) * 32 + (lane & 1), lds32(sb + R_MISC) * 32 + min(w + 1, 4 - (lane & 1)), 40);
            fence_acq();
            const uint4* fp = g_F + ((((wid >> 2) * 16 + h) * 4 + c) * 28 + 7 * w) * 224 + lane;
            uint4 w0[7];
#pragma unroll
            for (int m = 0; m < 7; m++) w0[m] = __ldcg(fp + m * 32);
#pragma unroll
            for (int k = 0; k < 6; k++)
#pragma unroll
                for (int m = 0; m < 7; m++) wr[m][k] = __ldcg(fp + (k + 1) * 224 + m * 32);
#pragma unroll
            for (int m = 0; m < 7; m++) { const uint4 v = movm4(w0[m]); sts128(sb + R_WB + wid * WB + lane * 16 + m * 512, v.x, v.y, v.z, v.w); }
#pragma unroll
            for (int k = 0; k < 6; k++)
#pragma unroll
                for (int m = 0; m < 7; m++) wr[m][k] = movm4(wr[m][k]);
            if (wid < 3) sts128(sb + R_STG + w * STGB + S_ONE + lane * 16, ONE2, ONE2, ONE2, ONE2);
            if (wid == 4) sts128(sb + R_WB + 4 * WB + W_QRT, 0x3e803e80u, 0x3e803e80u, 0x3e803e80u, 0x3e803e80u);
            cluster_wait();
        };
        if (wid < 4) {
            asm volatile("setmaxnreg.inc.sync.aligned.u32 248;");
            const int lane = fresh_lane(), g = lane >> 2;
            const uint32_t l16 = sb + lane * 16, l8 = sb + lane * 8;
            const uint32_t zr = lane & zero;
            uint4 wr[7][6];
            load_weights(wr, lane);
            const uint32_t r2 = uni(mapa(sb, 2) - mapa(sb, 0));
            const uint32_t uw = uni(R_WB + w * WB), uc = uni(R_WB + c * WB), u2 = uni((tile_of(w, 2) - 4 * w) * 128);
            const uint32_t upoll = uni(acc_off(w, 0, 0)), ured = uni(acc_off(c, w, 0)), uk = uni(S_KO + w * 1792), uv = uni(S_V + 4 * w * 512);
            const int src = 16 * (w & 1) + (lane >> 1);
            const uint32_t sia = sb + R_WB + W_SMI + (w >> 1) * 256 + src * 8;
            uint32_t lp = sb + (lane & 7) * 16 + (lane >> 4) * 128 + ((lane >> 3) & 1) * 256;
            {
                const uint32_t ua = sb + R_WB + (4 + (lane >> 3)) * WB + W_UP + (lane & 7) * 16 + 4 * w * 128;
                sts128u<W_TAB>(l16, uw, mapa(sb + R_SMM + (w < 2 ? c * 256 + src * 8 : 1024 + c * 128 + src * 4), rk + (lane & 1)), mapa(sb + R_BAR + B_SM, rk + (lane & 1)), acc_off(0, 0, lane), lp);
                sts128u<W_TAB + 512>(l16, uw, l8 + (((g ^ w) & 1) ? S_ONE : S_V + tile_of(w, 3) * 512), ua,
                                     ((lane ^ w) & 1) ? sb + R_WB + 4 * WB + W_QRT : ua + (tile_of(w, 3) - 4 * w) * 128,
                                     lp);
            }
            const bool wodd = w & 1;
            uint32_t t0 = clk() - POLL_DELAY;
            uint4 ub = make_uint4(0, 0, 0, 0);
            const uint8_t* pp = accb + acc_off(w, 0, lane);
            auto put_u = [&](int sl) {
                const uint32_t l4 = add_here(l8, -sb) >> 1;
                uint8_t* p = add_here((uint8_t*)(g_U + (((sl & (RS - 1)) * 64 + blockIdx.x) * 14 + 4 * w) * 32), l4);
                stg32(p, ub.x); stg32(p + 128, ub.y); stg32(p + (int)u2, ub.z);
                if (!(((l4 >> 4) ^ w) & 1)) stg32(p + (wodd ? -128 : 384), ub.w);
            };
            if (w == 3 && elect_one()) GT(0, 3);
            mbar_wait(sb + R_BAR + B_KV, 0);
            if (w == 3 && elect_one()) GT(0, 2);
#pragma unroll 1
            for (int s = 0; s < NSEG; s++) {
                const uint32_t par = uni((s & 1) * 2048), bar = uni(sb + R_BAR + s * 8), stg = uni(R_STG + (s % 3) * STGB), ksa = uni(stg + uk);
                uint4 w0[7];
                const uint4 ta = lds128u<W_TAB>(l16, uw);
                w0[0] = lds128u<0>(l16, uw); w0[1] = lds128u<512>(l16, uw); w0[2] = lds128u<1024>(l16, uw); w0[3] = lds128u<1536>(l16, uw);
                w0[4] = lds128u<2048>(l16, uw); w0[5] = lds128u<2560>(l16, uw); w0[6] = lds128u<3072>(l16, uw);
                const uint2 k3 = ldsm2u<1536>(l16, ksa);
                uint4 k0 = ldsm4u<0>(lp, ksa);
                const uint4 k1 = ldsm4u<512>(lp, ksa), k2 = ldsm4u<1024>(lp, ksa);
                while ((int)(clk() - t0) < POLL_DELAY) {}
                DBG(0);
                int it = zero;
                uint4 v0 = ld_relaxed4(pp), v1 = ld_relaxed4(pp + 2048), v2 = ld_relaxed4(pp + 16384), v3 = ld_relaxed4(pp + 18432);
                bar_arrive(BR_POLL + w, 64);
                {
                    sts128u<W_TAB + 1024>(l16, uw, ta.x + par, ta.y + s * 8, ta.x + par + r2, ta.y + s * 8 + r2);
                    const uint64_t rp = (uint64_t)(accb + (acc_slot(s + 1) + ured + ta.z)), pn = (uint64_t)(accb + (acc_slot(s + 1) + upoll + ta.z));
                    sts128u<W_TAB + 1536>(l16, uw, (uint32_t)rp, (uint32_t)(rp >> 32), (uint32_t)pn, (uint32_t)(pn >> 32));
                }
                if (s > 0 && !(EXP_MIN & 1)) put_u(s - 1);
                if (zero != 7) {
                bool ok;
#pragma unroll 1
                do {
                    if (it) {
                        if (it > SPIN) __trap();
                        v0 = ld_relaxed4(pp); v1 = ld_relaxed4(pp + 2048); v2 = ld_relaxed4(pp + 16384); v3 = ld_relaxed4(pp + 18432);
                    }
                    it++;
                    const uint32_t mn = min(min(v0.w, v1.w), v2.w), sel = 0x5410u ^ (mn & zr);
                    ok = __all_sync(0xffffffffu, mn >= CNT16 && v3.w >= CNT16);
                    v0.z ^= zr; v0.w = prmt(v0.w, v1.w, sel); v1.z ^= zr; v1.w = v3.z ^ (v0.w & zr); v2.z ^= zr; v2.w = prmt(v2.w, v3.w, sel);
                    sts128u<W_MB>(l16, uw, v0.x, v0.y, v0.z, v0.w); sts128u<W_MB + 512>(l16, uw, v1.x, v1.y, v1.z, v1.w);
                    sts128u<W_MB + 1024>(l16, uw, v2.x, v2.y, v2.z, v2.w); sts64u<W_MB + 1536>(l16, uw, v3.x, v3.y);
                } while (!ok);
                bar_sync(BR_MB, 256);
                }
                const uint32_t b[14] = {v0.x, v0.y, v0.z, v0.w, v1.x, v1.y, v1.z, v1.w, v2.x, v2.y, v2.z, v2.w, v3.x, v3.y};
                DBG(1);
                float acc[7][4], sa[4], sc[4], sx[4], sy[4];
                uint32_t tb[14];
                auto T = [&](int m, int k) { if (k == 0) mmaqz(acc[m], w0[m], b[0], b[1]); else mmaq(acc[m], wr[m][k - 1], b[2 * k], b[2 * k + 1]); };
                auto TR = [&](int m) { tb[2 * m] = movm(pack_bf16(acc[m][0], acc[m][1])); tb[2 * m + 1] = movm(pack_bf16(acc[m][2], acc[m][3])); };
                auto after = [&](uint32_t v, float dep) { return v ^ (__float_as_uint(dep) & zr); };
                T(6, 0); T(0, 0); T(1, 0); T(2, 0);
                T(6, 1); T(0, 1); T(1, 1); T(3, 0);
                T(6, 2); T(0, 2); T(1, 2); T(2, 1);
                T(6, 3); T(0, 3); T(1, 3); T(3, 1);
                T(6, 4); T(0, 4); T(1, 4); T(2, 2);
                T(6, 5); T(0, 5); T(1, 5); T(3, 2);
                T(6, 6); T(0, 6); T(1, 6); T(2, 3);
                w0[4].x = after(w0[4].x, acc[6][0]); w0[5].x = after(w0[5].x, acc[6][1]);
                const uint32_t ld = after(l16, acc[6][2]);
                uint4 am0 = lds128u<W_MB>(ld, uc);
                const uint2 am3 = lds64u<W_MB + 1536>(ld, uc);
                k0.x = after(k0.x, acc[1][0]);
                DBG(2);
                T(3, 3); T(4, 0); T(5, 0); T(2, 4);
                TR(6); TR(0); TR(1);
                T(3, 4); T(4, 1); T(5, 1); T(2, 5);
                T(3, 5); T(4, 2); T(5, 2); T(2, 6);
                T(3, 6); T(4, 3); T(5, 3);
                am0.x = after(am0.x, acc[2][0]);
                const uint32_t ld2 = after(l16, acc[2][1]);
                uint4 am1 = lds128u<W_MB + 512>(ld2, uc);
                const uint4 am2 = lds128u<W_MB + 1024>(ld2, uc);
                mmaqz(sx, k0, b[0], b[1]); mmaqz(sy, k0, b[2], b[3]);
                T(4, 4); T(5, 4);
                TR(2); TR(3);
                mmaqz(sa, am0, tb[0], tb[2]); mmaqz(sc, am0, tb[1], tb[3]);
                T(4, 5); T(5, 5);
                mmaq(sx, k1, b[4], b[5]); mmaq(sy, k1, b[6], b[7]);
                T(4, 6); T(5, 6);
                mma1688(sa, am3.x, am3.y, tb[12]); mma1688(sc, am3.x, am3.y, tb[13]);
                mmaq(sx, k2, b[8], b[9]); mmaq(sy, k2, b[10], b[11]);
                am1.x = after(am1.x, acc[4][0]);
                TR(4); TR(5);
                mmaq(sa, am1, tb[4], tb[6]); mmaq(sc, am1, tb[5], tb[7]);
                mma1688(sx, k3.x, k3.y, b[12]); mma1688(sy, k3.x, k3.y, b[13]);
                sts64u<W_SMI + 256>(l8, uw, __float_as_uint(sx[0] + sy[2]), __float_as_uint(sx[1] + sy[3]));
                const uint4 ra = lds128u<W_TAB + 1024>(l16, uw);
                bar_arrive((BR_GO + w) ^ (tb[GO_DEP] & zr), 64);
                mmaq(sa, am2, tb[8], tb[10]); mmaq(sc, am2, tb[9], tb[11]);
                sts64u<W_SMI>(l8, uw, __float_as_uint(sa[0] + sc[2]), __float_as_uint(sa[1] + sc[3]));
                DBG(3);
                bar_sync(BR_SM, 128);
                {
                    const float2 p0 = lds64f(sia), p1 = lds64f(sia + WB), p2 = lds64f(sia + 2 * WB), p3 = lds64f(sia + 3 * WB);
                    const float y0 = (p0.x + p1.x) + (p2.x + p3.x), y1 = (p0.y + p1.y) + (p2.y + p3.y);
                    st_async2_if(w < 2, ra.x, ra.y, y0, y1); st_async2_if(w < 2, ra.z, ra.w, y0, y1);
                    const uint32_t e = pack_bf16(ex2(y0), ex2(y1));
                    st_async1_if(w >= 2, ra.x, ra.y, e); st_async1_if(w >= 2, ra.z, ra.w, e);
                }
                DBG(4);
                const uint4 tc = lds128u<W_TAB + 512>(l16, uw);
                const uint4 td = lds128u<W_TAB + 1536>(l16, uw);
                const uint32_t va3 = tc.x, ua = tc.y, ua3 = tc.z, ea = tc.w;
                uint2 vb[4][2];
                auto load_v = [&]() {
                    const uint32_t va = stg + uv, va2 = va + 4 * u2;
                    vb[0][0] = lds64u<0>(l8, va); vb[1][0] = lds64u<512>(l8, va); vb[2][0] = lds64u<0>(l8, va2);
                    vb[0][1] = lds64u<256>(l8, va); vb[1][1] = lds64u<768>(l8, va); vb[2][1] = lds64u<256>(l8, va2);
                    vb[3][0] = lds64u<0>(va3, stg); vb[3][1] = lds64u<256>(va3, stg);
                };
                load_v();
                if (!(EXP_MIN & 4)) {
                stsm4u<S_TB - S_KO>(ea, ksa, tb[0], tb[2], tb[1], tb[3]); stsm4u<S_TB - S_KO + 512>(ea, ksa, tb[4], tb[6], tb[5], tb[7]);
                stsm4u<S_TB - S_KO + 1024>(ea, ksa, tb[8], tb[10], tb[9], tb[11]); stsm2u<S_TB - S_KO + 1536>(l16, ksa, tb[12], tb[13]);
                }
                float o[4][4];
                auto pv_x = [&](const uint4& e01, const uint4& e23) {
#pragma unroll
                    for (int q = 3; q < 7; q++) mmaqz(o[q & 3], e01, vb[q & 3][0].x, vb[q & 3][0].y);
#pragma unroll
                    for (int q = 3; q < 7; q++) mmaq(o[q & 3], e23, vb[q & 3][1].x, vb[q & 3][1].y);
                };
                auto pv_m = [&](float f0, float f1) {
                    const uint32_t pm = pack_bf16(f0, f1), j = __float_as_uint(f0);
                    mma1688(o[3], pm, j, ub.w); mma1688(o[0], pm, j, ub.x); mma1688(o[1], pm, j, ub.y); mma1688(o[2], pm, j, ub.z);
                };
                auto finish = [&](bool on) {
                    const float r = rcp(wodd ? o[3][0] : o[3][1]);
                    red_bf16x8((void*)(((uint64_t)td.y << 32) | td.x), on, pack_bf16(o[0][0] * r, o[0][1] * r), pack_bf16(o[1][0] * r, o[1][1] * r),
                               pack_bf16(o[2][0] * r, o[2][1] * r), pack_bf16((wodd ? o[3][1] : o[3][0]) * r, 1.0f));
                };
                mbar_wait_cl(bar + B_SM);
                DBG(5);
                float x0, x1;
                {
                    const uint4 e = ldsm4tu<R_SMM + 1024>(ea, par);
                    const float2 p0 = lds64fu<R_SMM>(l8, par), p1 = lds64fu<R_SMM + 256>(l8, par), p2 = lds64fu<R_SMM + 512>(l8, par), p3 = lds64fu<R_SMM + 768>(l8, par);
                    bar_sync(BR_UP, 256);
                    x0 = (p0.x + p1.x) + (p2.x + p3.x); x1 = (p0.y + p1.y) + (p2.y + p3.y);
                    pv_x(e, make_uint4(e.y ^ zr, __float_as_uint(x0), e.w ^ zr, __float_as_uint(x1)));
                }
                DBG(6);
                {
                    const float f0 = ex2(x0), f1 = ex2(x1);
                    const uint32_t a3 = UPIN == 2 ? ua3 : after(ua3, UPIN == 0 ? x0 : f0), a0 = UPIN == 2 ? ua : after(ua, UPIN == 0 ? x0 : f0);
                    const uint4 u3 = ldsm4q(a3), u0 = ldsm4q(a0), u1 = ldsm4q(a0 + 128), uu = ldsm4u<0>(a0, u2);
                    ub = make_uint4(hsum4(u0.x, u0.y, u0.z, u0.w), hsum4(u1.x, u1.y, u1.z, u1.w), hsum4(uu.x, uu.y, uu.z, uu.w), hsum4(u3.x, u3.y, u3.z, u3.w));
                    pv_m(f0, f1);
                }
                const bool safe = __all_sync(0xffffffffu, __float_as_uint(wodd ? o[3][0] : o[3][1]) - SAFE_LO < SAFE_SPAN);
                finish(safe);
                if (!safe) {
                    float y[8];
#pragma unroll
                    for (int q = 0; q < 8; q++) {
                        const uint32_t ln = add_here(l8, -sb) >> 3;
                        const uint32_t a = mapa(sb + R_WB + W_SMI + 256 + (2 * (ln & 3) + (q & 1)) * 32 + (ln >> 2) * 4, rk + (q >> 1));
                        y[q] = (ldr32f(a) + ldr32f(a + WB)) + (ldr32f(a + 2 * WB) + ldr32f(a + 3 * WB));
                    }
                    float m = fmaxf(x0, x1);
#pragma unroll
                    for (int q = 0; q < 8; q++) m = fmaxf(m, y[q]);
                    m = fmaxf(m, __shfl_xor_sync(0xffffffffu, m, 1)); m = fmaxf(m, __shfl_xor_sync(0xffffffffu, m, 2));
                    load_v();
                    pv_x(make_uint4(pack_bf16(ex2(y[0] - m), ex2(y[1] - m)), 0u, pack_bf16(ex2(y[2] - m), ex2(y[3] - m)), 0u),
                         make_uint4(pack_bf16(ex2(y[4] - m), ex2(y[5] - m)), 0u, pack_bf16(ex2(y[6] - m), ex2(y[7] - m)), 0u));
                    pv_m(ex2(x0 - m), ex2(x1 - m));
                    finish(zero == 0);
                }
                t0 = clk();
                DBG(9);
                bar_arrive(BR_RED, 256);
                pp = (const uint8_t*)(((uint64_t)td.w << 32) | td.z);
                lp = ea;
                mbar_wait(bar + (s < NSEG - 1 ? B_KV + 8 : B_KV), 0);
            }
            bar_arrive(BR_POLL + w, 64);
            put_u(NSEG - 1);
            bar_arrive(BR_PRO, 160);
        } else {
            const int lane = fresh_lane(), g = lane >> 2, t = lane & 3;
            const uint32_t l16 = sb + lane * 16, l8 = sb + lane * 8, wsa = l16 + R_WB + wid * WB;
            uint4 wr[7][6];
            load_weights(wr, lane);
            auto softmax_rows = [&](int sl, bool gate) {
                float v[10];
                const uint32_t a = R_LS + (sl & 1) * 5120;
                const float4 q0 = sum4(lds128f(l16 + a), lds128f(l16 + a + 1280), lds128f(l16 + a + 2560), lds128f(l16 + a + 3840));
                const float4 q1 = sum4(lds128f(l16 + a + 512), lds128f(l16 + a + 1792), lds128f(l16 + a + 3072), lds128f(l16 + a + 4352));
                const float2 p0 = lds64f(l8 + a + 1024), p1 = lds64f(l8 + a + 2304), p2 = lds64f(l8 + a + 3584), p3 = lds64f(l8 + a + 4864);
                const float z[8] = {q0.x, q0.y, q0.z, q0.w, q1.x, q1.y, q1.z, q1.w};
                v[8] = (p0.x + p1.x) + (p2.x + p3.x); v[9] = (p0.y + p1.y) + (p2.y + p3.y);
                const int lim = 8 * c + g - 2 * t;
#pragma unroll
                for (int i = 0; i < 8; i++) v[i] = (8 * (i >> 1) + (i & 1) <= lim) ? z[i] : -INFINITY;
                float e[10], l[4];
                auto expo = [&](float m) {
#pragma unroll
                    for (int i = 0; i < 10; i++) e[i] = ex2(v[i] - m);
                    mma16816z(l, pack_bf16(e[0], e[1]), pack_bf16(e[4], e[5]), pack_bf16(e[2], e[3]), pack_bf16(e[6], e[7]), ONE2, ONE2);
                    mma1688(l, pack_bf16(e[8], e[9]), 0u, ONE2);
                    l[0] += l[2];
                };
                expo(0.f);
                if (__builtin_expect(__any_sync(0xffffffffu, __float_as_uint(l[0]) - SAFE_LO >= SAFE_SPAN), 0)) {
                    float m = v[0];
#pragma unroll
                    for (int i = 1; i < 10; i++) m = fmaxf(m, v[i]);
                    m = fmaxf(m, __shfl_xor_sync(0xffffffffu, m, 1)); m = fmaxf(m, __shfl_xor_sync(0xffffffffu, m, 2));
                    expo(m);
                }
                const float r = rcp(l[0]);
                uint8_t* pd = add_here((uint8_t*)(g_P + (((sl & (RS - 1)) * 16 + h) * 14 + (c * (c + 3) >> 1)) * 32), lane * 4);
                if (gate) bar_sync((BR_POLL + 2) ^ (__float_as_uint(r) & zero), 64);
#pragma unroll
                for (int q = 0; q < 4; q++) if (q <= c) stg32(pd + q * 128, pack_bf16(e[2 * q] * r, e[2 * q + 1] * r));
                stg32(pd + (c + 1) * 128, pack_bf16(e[8] * r, e[9] * r));
                __syncwarp();
                mbar_arrive_if(lane == 0, sb + R_BAR + B_PUB + sl * 8);
            };
            uint4 wx[URES + 1];
#pragma unroll
            for (int m = 0; m < URES; m++) wx[m] = lds128(wsa + m * 512);
            bar_sync(BR_POLL + w, 64);
#pragma unroll 1
            for (int s = 0; s < NSEG; s++) {
                const uint32_t stg = R_STG + (s % 3) * STGB;
                uint4 w0[7];
#pragma unroll
                for (int m = 0; m < 7 - UW0; m++) w0[m] = m < URES ? wx[m] : lds128(wsa + m * 512);
                bar_sync(BR_MB, 256);
                mbar_arrive_if(lane + w == 0, sb + R_BAR + B_H + s * 8);
                const uint32_t ba = wsa - 4 * WB + W_MB;
                const uint4 b0 = lds128(ba), b1 = lds128(ba + 512), b2 = lds128(ba + 1024);
                const uint2 b3 = lds64(ba + 1536);
#pragma unroll
                for (int m = 7 - UW0; m < 7; m++) w0[m] = lds128(wsa + m * 512);
                bar_sync(BR_GO + w, 64);
                SCHED_FENCE(zero, 2);
                DBG(11);
                float acc[7][4];
                const uint32_t b[14] = {b0.x, b0.y, b0.z, b0.w, b1.x, b1.y, b1.z, b1.w, b2.x, b2.y, b2.z, b2.w, b3.x, b3.y};
                auto U = [&](int m, int k) { if (k == 0) mmaqz(acc[m], w0[m], b[0], b[1]); else mmaq(acc[m], wr[m][k - 1], b[2 * k], b[2 * k + 1]); };
#pragma unroll
                for (int k = 0; k < 7; k++) { U(0, k); U(1, k); U(6, k); U(2 + (k & 3), k >> 2); }
                wr[5][0].x ^= __float_as_uint(acc[0][0]) & zero; wr[2][1].x ^= __float_as_uint(acc[1][0]) & zero;
                wr[3][1].x ^= __float_as_uint(acc[6][0]) & zero; wr[4][1].x ^= __float_as_uint(acc[6][1]) & zero;
                U(5, 1);
#pragma unroll
                for (int k = 2; k < 7; k++) { U(2, k); U(3, k); U(4, k); U(5, k); }
                {
                    const uint32_t a = wsa + W_UP;
                    stsm2(a + 1536, pack_bf16(acc[6][0], acc[6][1]), pack_bf16(acc[6][2], acc[6][3]));
#pragma unroll
                    for (int q = 0; q < 3; q++)
                        stsm4(a + q * 512, make_uint4(pack_bf16(acc[2 * q][0], acc[2 * q][1]), pack_bf16(acc[2 * q][2], acc[2 * q][3]),
                                                      pack_bf16(acc[2 * q + 1][0], acc[2 * q + 1][1]), pack_bf16(acc[2 * q + 1][2], acc[2 * q + 1][3])));
                }
                bar_arrive(BR_UP, 256);
                DBG(12);
                if (w == 2 && s > 0 && !(EXP_MIN & 2)) mbar_wait_cl(sb + R_BAR + B_LS + (s - 1) * 8);
                bar_sync(BR_RED, 256);
                if (EXP_MIN & 2) { bar_sync(BR_POLL + w, 64); mbar_arrive_if(lane == 0 && w == 2, sb + R_BAR + B_PUB + s * 8); } else
                {
                    float y[32];
                    const uint64_t da = sdesc(sb + stg + S_X, 16, 1024, 1), db = sdesc(sb + stg + S_KS, 128, 1792, 0);
                    asm volatile("fence.proxy.async.shared::cta;" ::: "memory");
                    wg_fence();
#pragma unroll
                    for (int k = 0; k < 7; k++) wgmma64(y, da + (k >> 2) * 256 + (k & 3) * 2, db + k * 16, k);
                    wg_commit();
                    wg_wait<0>();
                    if (w < 2) {
                        const uint32_t r0 = mapa(sb, rk + 2 * w), r1 = mapa(sb, rk + 2 * w + 1);
                        const uint32_t o = R_LS + (s & 1) * 5120 + c * 1280 + lane * 16, lb = R_BAR + B_LS + s * 8;
                        bar_sync(BR_POLL + w, 64);
                        st_async4(r0 + o, r0 + lb, y[0], y[1], y[4], y[5]); st_async4(r1 + o, r1 + lb, y[2], y[3], y[6], y[7]);
                        if (w == 1) { st_async4(r0 + o + 512, r0 + lb, y[8], y[9], y[12], y[13]); st_async4(r1 + o + 512, r1 + lb, y[10], y[11], y[14], y[15]); }
                        st_async2(r0 + o + 1024 - lane * 8, r0 + lb, (y[16] + y[20]) + (y[24] + y[28]), (y[17] + y[21]) + (y[25] + y[29]));
                        st_async2(r1 + o + 1024 - lane * 8, r1 + lb, (y[18] + y[22]) + (y[26] + y[30]), (y[19] + y[23]) + (y[27] + y[31]));
                    } else if (w == 2 && s > 0) softmax_rows(s - 1, true);
                    else {
                        if (s >= 3) mbar_wait(sb + R_BAR + B_Z + (s - 3) * 8, 0);
                        bar_sync(BR_POLL + w, 64);
                    }
                }
                DBG(13);
                DBG(14);
            }
            if (EXP_MIN & 2) { if (w == 2) bar_sync(BR_PRO, 160); } else
            if (w == 2) { bar_sync(BR_PRO, 160); mbar_wait_cl(sb + R_BAR + B_LS + (NSEG - 1) * 8); softmax_rows(NSEG - 1, false); }
        }
        cluster_arrive_rel(); cluster_wait();
    } else {
        asm volatile("setmaxnreg.dec.sync.aligned.u32 24;");
        const unsigned epoch = uni(ld_relaxed(&g_EXIT) / ntotal);
        const int lane = fresh_lane();
        if (elect_one()) {
#pragma unroll 1
            for (int i = w; i < 384; i += 4) {
                mbar_init(sb + R_BAR + i * 8, TRIG_DELAY && (i >> 6) == 3 ? 4 : 1);
                if (i < 192) mbar_expect(sb + R_BAR + i * 8, i < 64 ? S_TB : (i < 128 ? 1536 : (c < 2 ? 3072 : 5120)));
            }
            asm volatile("fence.mbarrier_init.release.cluster;" ::: "memory");
            asm volatile("fence.proxy.async.shared::cta;" ::: "memory");
        }
        __syncwarp();
        bar_sync(BR_H, 128);
        cluster_arrive();
        if (w == 0) {
            sts32(sb + R_MISC, epoch);
            wait_count_warp(&g_INIT, (epoch + 1) * 64, 100);
            fence_acq();
            bar_sync(BR_ALL, 288);
            const unsigned* ft = g_FT + (lane < 2 ? 2 * h + lane : 32 + 2 * h + (c >> 1)) * 32;
#pragma unroll 1
            for (int seg = 0; seg < NSEG; seg++) {
                if (!(seg & 1)) {
                    wait_count_warp(ft + (~(seg >> 1) & 1), epoch * 32 + (((seg >> 1) + 9) >> 1), seg ? 0 : 40);
                    fence_acq();
                    asm volatile("fence.proxy.async.global;" ::: "memory");
                }
                const uint32_t bar = sb + R_BAR + B_KV + seg * 8, dst = sb + R_STG + (seg % 3) * STGB;
                const uint8_t* kp = g_K + ((seg & (RS - 1)) * 16 + h) * 28672;
                const uint8_t* vp = g_V + (((seg & (RS - 1)) * 16 + h) * 4 + c) * 7168;
                if (seg == 0 && elect_one()) GT(0, 7);
                if (seg >= 2) mbar_wait(sb + R_BAR + B_H + (seg - 2) * 8, 0);
                if (elect_one()) {
                    bulk_g2s(dst + S_KO, kp + c * 7168, 7168, bar);
                    bulk_g2s(dst + S_V, vp, 7168, bar);
                    tma2d(dst + S_X, &mapXs, 112 * c, 32 * seg, bar); tma2d(dst + S_X + 4096, &mapXs, 112 * c + 64, 32 * seg, bar);
#pragma unroll
                    for (int j = 0; j < 4; j++) bulk_g2s(dst + S_KS + j * 1792, kp + j * 7168 + c * 1792, 1792, bar);
                }
                if (seg == 2 && elect_one()) GT(0, 4);
                if (seg == NSEG - 1 && elect_one()) GT(0, 5);
            }
        } else if (w == 1) {
            {
                const int q = h >> 2, l = (h & 3) * 8 + (lane & 7);
                const uint32_t* mp = (const uint32_t*)(mem0 + (l >> 2) * D + 112 * c) + (l & 3);
                uint4 v = make_uint4(0, 0, 0, 0);
                if (lane < 8) v = make_uint4(mp[4 * tile_of(q, 0)], mp[4 * tile_of(q, 1)], mp[4 * tile_of(q, 2)],
                                             ((mp[4 * tile_of(q, 3)] >> (16 * (q & 1))) & 0xffffu) | CNT16);
                *(uint4*)(accb + acc_off(c, q, l) + acc_slot(lane >> 3)) = v;
                *(uint4*)(accb + acc_off(c, q, l) + acc_slot(4 + (lane >> 3))) = make_uint4(0, 0, 0, 0);
                __syncwarp();
                if (lane == 0) { fence_rel(); red_inc(&g_INIT); }
            }
            __syncwarp();
            uint8_t* zp = accb + acc_off(c, h >> 2, (h & 3) * 8 + (lane & 7));
#pragma unroll 1
            for (int seg = 0; seg < NSEG; seg++) {
                mbar_wait(sb + R_BAR + B_PUB + seg * 8, 0);
                if (lane < 8 && seg < NSEG - 8 + ((EXP_MIN >> 1) & 1) && seg >= ((EXP_MIN >> 1) & 1)) *(uint4*)(zp + acc_slot(seg - ((EXP_MIN >> 1) & 1))) = make_uint4(0, 0, 0, 0);
                __syncwarp();
                if (lane == 0) {
                    fence_rel();
                    red_inc(g_CNT + seg * 32); mbar_arrive(sb + R_BAR + B_Z + seg * 8); }
                __syncwarp();
            }
            if (elect_one()) GT(0, 6);
        } else {
            if (w == 2 && PF2) {
                const uint32_t t1 = clk();
                while ((int)(clk() - t1) < PF2) __nanosleep(100);
                if (elect_one()) {
#pragma unroll 1
                    for (int i = 1; i < 7; i++) { prefetch_l2(wk + (i * 64 + blockIdx.x) * 8192, 8192); prefetch_l2(wv + (i * 64 + blockIdx.x) * 8192, 8192); }
                    prefetch_l2(x + blockIdx.x * 28672, 28672);
                }
            }
            if (w == 3 && blockIdx.x < D / 8) {
#pragma unroll 1
                for (int i = 0; i < 16; i++) {
                    mbar_wait(sb + R_BAR + B_H + i * 8, 0);
                    if (elect_one()) { ssm_store(sb, blockIdx.x * 8, i, &mapY); asm volatile("cp.async.bulk.wait_group 0;" ::: "memory"); }
                    __syncwarp();
                }
            }
        }
        cluster_wait(); cluster_arrive(); cluster_wait();
        if (w == 1 && lane == 0) red_inc(&g_EXIT);
    }
}

constexpr int BLK = 28672;
#define NRING 6
constexpr int G_RING = 7 * BLK;
constexpr int G_SCR = G_RING + NRING * 4096;
constexpr int G_BAR = G_SCR + 6144;
constexpr int G_PUB = G_BAR + 18 * 8;
constexpr int G_RDY = G_PUB + 39 * 8;
constexpr int G_MISC = G_RDY + 8 * 8;
constexpr int G_SMEM = G_MISC + 16;
static_assert(G_SMEM <= 232448, "smem");
#define FPACE 70
#define PACE 120
constexpr int LAG = 4, TAIL = NSEG - 8;
static_assert(LAG + 3 <= RS / 2, "ring");
constexpr int PVS = 37632, PV_U = 28672, PV_P = 35840, PV_N = 6, PV_Z = PV_N * PVS;
static_assert(PV_Z + 16 <= G_BAR, "smem");

struct PvOps { uint2 v[2][14]; uint32_t p[2][14], m[2][7]; };
__device__ __forceinline__ void pv_load_v(PvOps& o, int sh, int G, int lane) {
    const uint8_t* vp = g_V + (sh * 56 + 7 * G) * 512 + lane * 8;
#pragma unroll
    for (int i = 0; i < 28; i++) o.v[i / 14][i % 14] = __ldcg((const uint2*)(vp + (i / 14) * (56 * 512) + (i % 14) * 256));
}
__device__ __forceinline__ void pv_load_pu(PvOps& o, int sh, int G, int lane) {
    const uint32_t* up = g_U + (sh * 56 + 7 * G) * 32 + lane;
    const uint32_t* pp = g_P + sh * 448 + lane;
#pragma unroll
    for (int i = 0; i < 28; i++) o.p[i / 14][i % 14] = __ldcg(pp + i * 32);
#pragma unroll
    for (int i = 0; i < 14; i++) o.m[i / 7][i % 7] = __ldcg(up + (i / 7) * (56 * 32) + (i % 7) * 32);
}
__device__ __forceinline__ void pv_mma(float (&acc)[2][7][4], const PvOps& o) {
#pragma unroll
    for (int j = 0; j < 2; j++) {
        const uint32_t* q = o.p[j];
#pragma unroll
        for (int i = 0; i < 7; i++) mma16816(acc[1][i], q[5], q[9], q[6], q[10], o.v[j][2 * i].x, o.v[j][2 * i].y);
#pragma unroll
        for (int i = 0; i < 7; i++) mma16816(acc[0][i], q[0], q[2], 0u, q[3], o.v[j][2 * i].x, o.v[j][2 * i].y);
#pragma unroll
        for (int i = 0; i < 7; i++) mma16816(acc[1][i], q[7], q[11], 0u, q[12], o.v[j][2 * i + 1].x, o.v[j][2 * i + 1].y);
    }
#pragma unroll
    for (int i = 0; i < 7; i++) {
        mma16816(acc[0][i], o.p[0][1], o.p[0][4], o.p[1][1], o.p[1][4], o.m[0][i], o.m[1][i]);
        mma16816(acc[1][i], o.p[0][8], o.p[0][13], o.p[1][8], o.p[1][13], o.m[0][i], o.m[1][i]);
    }
}
__device__ __forceinline__ int unit_segment(int n, int k, bool spare) { return spare ? (n < 32 ? 16 * k + 4 * (n >> 3) + 3 : NSEG) : 8 * k + (n >> 3); }

__device__ __forceinline__ void pace(uint32_t& t0, int gap) { uint32_t t1; do { t1 = clk(); } while ((int)(t1 - t0) < 0); t0 = t1 + gap; }

template <int NSTG>
__device__ __forceinline__ void tile_mainloop(float* d, uint32_t sb, int slot, uint32_t par, uint64_t db, uint32_t kstep, bool trans,
                                              int lane, int pass_to, bool wait_b) {
    const uint64_t da0 = sdesc(sb + G_RING, 16, 512, 2);
    const uint32_t eb = mapa(sb + G_BAR + 7 * 8, lane & 1);
    int prev = 0;
#pragma unroll
    for (int i = 0; i < NSTG; i++) {
        if (!(i & 1) && wait_b) mbar_wait(sb + G_BAR + (14 + (i >> 1)) * 8, 0);
        mbar_wait(sb + G_BAR + slot * 8, par);
        wg_fence();
        const uint64_t da = da0 + slot * 256, b0 = db + (i >> 1) * (BLK >> 4) + (i & 1) * 2 * kstep;
        if (trans) { wgmma224<1>(d, da, b0, i); wgmma224<1>(d, da + 2, b0 + kstep, 1); }
        else { wgmma224<0>(d, da, b0, i); wgmma224<0>(d, da + 2, b0 + kstep, 1); }
        wg_commit();
        if (i == NSTG - 1 && pass_to) bar_arrive(pass_to, 256);
        if (i > 0) { wg_wait<1>(); mbar_arrive_cl_if(lane < 2, eb + prev * 8); }
        prev = slot;
        if (++slot == NRING) { slot = 0; par ^= 1; }
    }
    wg_wait<0>();
    mbar_arrive_cl_if(lane < 2, eb + prev * 8);
}

template <int M>
__device__ __forceinline__ void fold_role(uint32_t sb, int n, int wg, int u, int lane) {
    const bool lead = lane == 0;
    const uint64_t db = M == 0 ? sdesc(sb + 3 * BLK, 16, 1024, 1) : sdesc(sb + 3 * BLK, 4096, 512, 2);
    const uint32_t sa = sb + (8 * ((lane >> 3) & 1) + (lane & 7)) * 128 + (((2 * u + (lane >> 4)) ^ (lane & 7)) << 4);
    uint4* dst = g_F + (n * 56 + 4 * wg + u) * 224 + lane;
    uint4 q[14], qa[14];
#pragma unroll
    for (int i = 0; i < 14; i++) q[i] = make_uint4(0, 0, 0, 0);
    int blk = wg;
#pragma unroll 1
    for (;; blk += 2, dst += 8 * 224) {
        float d[112];
        bar_sync(1 + wg, 256);
        tile_mainloop<8>(d, sb, (8 * blk) % NRING, ((8 * blk) / NRING) & 1, db, M == 0 ? 2 : 64, M == 1, lane, 2 - wg, blk < 2);
        if (u == 0 && lead) GT(1, 6 + blk);
        const float sc = M ? 1.f : 0.0625f * LOG2E;
#pragma unroll
        for (int i = 0; i < 14; i++) {
            const float* e = d + 8 * i;
            qa[i] = q[i];
            q[i] = make_uint4(pack_bf16(e[0] * sc, e[1] * sc), pack_bf16(e[4] * sc, e[5] * sc), pack_bf16(e[2] * sc, e[3] * sc), pack_bf16(e[6] * sc, e[7] * sc));
        }
        auto handover = [&]() {
            bar_sync(3, 256);
#pragma unroll
            for (int i = 0; i < 14; i++) { stsm4t(sa + (blk - 2) * BLK + i * 2048, qa[i]); stsm4t(sa + blk * BLK + i * 2048, q[i]); }
            asm volatile("fence.proxy.async.shared::cta;" ::: "memory");
            bar_sync(3, 256);
        };
        if (blk == 6) { handover(); if (u == 0 && lead) GT(1, 13); }
        uint32_t t0 = clk();
#pragma unroll
        for (int i = 0; i < 14; i++) {
            pace(t0, FPACE);
            dst[(i / 7) * (28 * 224) + (i % 7) * 32] = q[i];
            if (blk < 3) stsm4t(sa + blk * BLK + i * 2048, q[i]);
        }
        __syncwarp();
        mbar_arrive_if(lead, sb + G_PUB + blk * 8);
        if (blk == 5) handover();
        if (blk >= 5) break;
    }
}

__device__ __forceinline__ void bulk_consumer(uint32_t sb, int n, unsigned epoch, __nv_bfloat16* __restrict__ out, int phases, bool spare) {
    const int lane = fresh_lane(), wid = __shfl_sync(0xffffffffu, threadIdx.x >> 5, 0), wg = wid >> 2, u = wid & 3;
    const int h = (n >> 1) & 15, hf = n & 1;
    const bool lead = lane == 0;
    if (phases & 1) {
        if (wg == 1) bar_arrive(1, 256);
        if (n < 32) fold_role<0>(sb, n, wg, u, lane); else fold_role<1>(sb, n, wg, u, lane);
        bar_sync(1 + wg, 256);
    }
    const uint64_t db = sdesc(sb, 16, 1024, 1);
    float acc[2][7][4];
#pragma unroll
    for (int i = 0; i < 56; i++) (&acc[0][0][0])[i] = 0.f;
#pragma unroll 1
    for (int tile = 1 - wg; tile < LAG + TAIL / 2 + 5; tile += 2) {
        const bool gemm = tile < 32 && (phases & 1);
        uint32_t y[56];
        if (gemm) {
            float d[112];
            tile_mainloop<14>(d, sb, (56 + 14 * tile) % NRING, ((56 + 14 * tile) / NRING) & 1, db, 2, false, lane, tile == 31 ? 0 : 2 - wg, false);
#pragma unroll
            for (int i = 0; i < 56; i++) y[i] = pack_bf16(d[2 * i], d[2 * i + 1]);
        } else {
#pragma unroll
            for (int i = 0; i < 56; i++) y[i] = 0;
        }
        const int lp = spare ? 3 : 2, rel = tile - LAG - (unit_segment(n, 0, spare) >> 1), ph = rel & ((1 << lp) - 1);
        const int useg = unit_segment(n, rel >> lp, spare), pseg = unit_segment(n, (rel - 4) >> lp, spare);
        const bool batch = rel >= 0 && (ph == 0 || ph == 2) && useg < TAIL && (phases & 2);
        PvOps ops;
        if (batch) {
            if (ph == 0) mbar_wait(sb + G_RDY + (rel >> lp) * 8, 0);
            const int sh = (useg & (RS - 1)) * 16 + 4 * u + ph;
            pv_load_v(ops, sh, n & 7, lane); pv_load_pu(ops, sh, n & 7, lane);
        } else {
#pragma unroll
            for (int j = 0; j < 2; j++) {
#pragma unroll
                for (int i = 0; i < 14; i++) { ops.v[j][i] = make_uint2(0u, 0u); ops.p[j][i] = 0u; if (i < 7) ops.m[j][i] = 0u; }
            }
        }
        if (gemm) {
            const int slot = (2 * tile + (u >> 1)) & (RS - 1);
            if (tile >= RS / 2)
                wait_count_warp(n < 32 ? g_CNT + (2 * tile + 1 - RS) * 32 : g_WD + (tile - RS / 2) * 32, (epoch + 1) * 64, 100);
            uint32_t t0 = clk();
            const int gap = tile > 1 && !batch ? PACE : FPACE;
            if (n < 32) {
                uint8_t* rec = g_K + (((slot * 16 + h) * 4 + 2 * (u & 1)) * 56 + 28 * hf) * 128 + lane * 4;
#pragma unroll
                for (int i = 0; i < 28; i++) {
                    if (!(i & 1)) pace(t0, gap);
                    stg32(rec + i * 128, y[2 * i]); stg32(rec + 7168 + i * 128, y[2 * i + 1]);
                }
            } else {
                uint8_t* rec = g_V + ((slot * 16 + h) * 56 + 28 * hf) * 512 + (u & 1) * 256 + lane * 8;
#pragma unroll
                for (int i = 0; i < 28; i++) {
                    if (!(i & 1)) pace(t0, gap);
                    *(uint2*)(rec + i * 512) = make_uint2(movm(y[2 * i]), movm(y[2 * i + 1]));
                }
            }
            __syncwarp();
            mbar_arrive_if(lead, sb + G_PUB + (7 + tile) * 8);
        }
        if (rel >= 4 && ph == (4 & ((1 << lp) - 1)) && pseg < TAIL && (phases & 2)) {
            uint32_t* o = (uint32_t*)(out + (size_t)(pseg * 32 + 8 * u + (lane >> 2)) * OUTW + D + 56 * (n & 7)) + (lane & 3);
            const uint32_t sc = sb + G_SCR + lane * 16;
#pragma unroll
            for (int i = 0; i < 7; i += 2) {
                const int i1 = i < 6 ? i + 1 : i;
                float4 own = make_float4(0.f, 0.f, 0.f, 0.f);
#pragma unroll
                for (int r = 0; r < 4; r++) {
                    const float* a = acc[r >> 1][i] + 2 * (r & 1); const float* b = acc[r >> 1][i1] + 2 * (r & 1);
                    if (r == u) own = make_float4(a[0], a[1], b[0], b[1]);
                    else sts128(sc + (r * 3 + ((u - r - 1) & 3)) * 512, __float_as_uint(a[0]), __float_as_uint(a[1]), __float_as_uint(b[0]), __float_as_uint(b[1]));
                }
                bar_sync(4, 128);
                const float4 z = sum4(own, lds128f(sc + u * 1536), lds128f(sc + u * 1536 + 512), lds128f(sc + u * 1536 + 1024));
                bar_sync(4, 128);
                o[4 * i] = pack_bf16(z.x, z.y);
                if (i < 6) o[4 * i + 4] = pack_bf16(z.z, z.w);
            }
#pragma unroll
            for (int i = 0; i < 56; i++) (&acc[0][0][0])[i] = 0.f;
        }
        if (tile < 30 && (phases & 1)) bar_sync(1 + wg, 256);
        if (batch) {
            pv_mma(acc, ops);
            if (ph == 2 && lead) red_add(g_WD + (useg >> 1) * 32 + (__float_as_uint(acc[1][6][0]) & (phases >> 8)), 1);
        }
    }
    cluster_arrive_rel();
    if (!(phases & 2)) return;
    const int seg = TAIL + (n >> 3), sh = (seg & (RS - 1)) * 16 + 2 * wid, q = 7 + (seg >> 1);
    wait_count_warp(g_FT + (32 + 4 * wid + 2 * (lane & 1) + ((n >> 2) & 1)) * 32 + (q & 1), epoch * 32 + (q >> 1) + 1, 50);
    fence_acq();
    PvOps ops;
    pv_load_v(ops, sh, n & 7, lane);
    bar_sync(3, 256);
    mbar_wait(sb + G_RDY + 7 * 8, 0);
    pv_load_pu(ops, sh, n & 7, lane);
    pv_mma(acc, ops);
    const uint32_t wa = sb + wid * 7168 + (lane >> 2) * 224 + (lane & 3) * 8;
#pragma unroll
    for (int i = 0; i < 14; i++) { const float* a = acc[i / 7][i % 7]; sts64f(wa + (i / 7) * 3584 + (i % 7) * 32, a[0], a[1]); sts64f(wa + (i / 7) * 3584 + 1792 + (i % 7) * 32, a[2], a[3]); }
    bar_sync(3, 256);
    if (wid < 7) {
        const int i = wid * 32 + lane, r = i / 7;
        const uint32_t a = sb + i * 32;
        float4 x[2];
#pragma unroll
        for (int j = 0; j < 2; j++) {
            const float4 lo = sum4(lds128f(a + 16 * j), lds128f(a + 16 * j + 7168), lds128f(a + 16 * j + 2 * 7168), lds128f(a + 16 * j + 3 * 7168));
            const float4 hi = sum4(lds128f(a + 16 * j + 4 * 7168), lds128f(a + 16 * j + 5 * 7168), lds128f(a + 16 * j + 6 * 7168), lds128f(a + 16 * j + 7 * 7168));
            x[j] = make_float4(lo.x + hi.x, lo.y + hi.y, lo.z + hi.z, lo.w + hi.w);
        }
        *(uint4*)(out + (size_t)(seg * 32 + r) * OUTW + D + 56 * (n & 7) + 8 * (i - 7 * r)) =
            make_uint4(pack_bf16(x[0].x, x[0].y), pack_bf16(x[0].z, x[0].w), pack_bf16(x[1].x, x[1].y), pack_bf16(x[1].z, x[1].w));
    }
}

__device__ __forceinline__ int spare_segment(int i) { return i + i / 3; }
__device__ __forceinline__ void spare_consumer(uint32_t sb, int j, __nv_bfloat16* __restrict__ out) {
    const int lane = fresh_lane(), wid = __shfl_sync(0xffffffffu, threadIdx.x >> 5, 0), mi = lane >> 3;
    if (wid == 0) sts128(sb + PV_Z, 0u, 0u, 0u, 0u);
    bar_sync(3, 256);
    const uint32_t row = sb + (lane & 7) * 16, va = sb + wid * 3584 + lane * 8, ua = sb + PV_U + wid * 896 + lane * 16;
    const uint32_t pa[4] = {row + PV_P + ((0x3020 >> (4 * mi)) & 15) * 128, row + PV_P + ((0xa695 >> (4 * mi)) & 15) * 128,
                            row + PV_P + ((0xc0b7 >> (4 * mi)) & 15) * 128, row + PV_P + ((0xd841 >> (4 * mi)) & 15) * 128};
    int slot = 0; uint32_t par = 0;
#pragma unroll 1
    for (int i = j; spare_segment(i) < TAIL; i += 4) {
        const int seg = spare_segment(i);
        float acc[2][7][4];
#pragma unroll
        for (int k = 0; k < 56; k++) (&acc[0][0][0])[k] = 0.f;
#pragma unroll 1
        for (int h = 0; h < 16; h++) {
            const uint32_t so = slot * PVS;
            mbar_wait(sb + G_BAR + slot * 8, par);
            const uint4 q0 = ldsm4q(mi == 2 ? sb + PV_Z : pa[0] + so), q1 = ldsm4q(pa[1] + so), q2 = ldsm4q(mi == 2 ? sb + PV_Z : pa[2] + so), q3 = ldsm4q(pa[3] + so);
            const uint4 m0 = ldsm4q(ua + so), m1 = ldsm4q(ua + so + 384);
            const uint32_t m[7] = {m0.x, m0.y, m0.z, m1.x, m1.y, m1.z, m1.w};
            uint2 v[14];
#pragma unroll
            for (int k = 0; k < 14; k++) v[k] = lds64(va + so + k * 256);
#pragma unroll
            for (int k = 0; k < 7; k++) { mmaq(acc[1][k], q1, v[2 * k].x, v[2 * k].y); mmaq(acc[0][k], q0, v[2 * k].x, v[2 * k].y); }
#pragma unroll
            for (int k = 0; k < 7; k++) { mmaq(acc[1][k], q2, v[2 * k + 1].x, v[2 * k + 1].y); mma1688(acc[0][k], q3.x, q3.y, m[k]); }
#pragma unroll
            for (int k = 0; k < 7; k++) mma1688(acc[1][k], q3.z, q3.w, m[k]);
            __syncwarp();
            mbar_arrive_if(lane == 0, sb + G_BAR + (7 + slot) * 8);
            if (++slot == PV_N) { slot = 0; par ^= 1; }
        }
        if (lane == 0) red_add(g_WD + (seg >> 1) * 32, 4);
        uint32_t* o = (uint32_t*)(out + (size_t)(seg * 32 + (lane >> 2)) * OUTW + D + 56 * wid) + (lane & 3);
#pragma unroll
        for (int k = 0; k < 28; k++) o[(k / 7) * (8 * OUTW / 2) + 4 * (k % 7)] = pack_bf16(acc[k / 14][k % 7][2 * ((k / 7) & 1)], acc[k / 14][k % 7][2 * ((k / 7) & 1) + 1]);
    }
}

__global__ void __cluster_dims__(2, 1, 1) __launch_bounds__(384, 1)
k_bulk(const __grid_constant__ CUtensorMap mapX, const __grid_constant__ CUtensorMap mapK, const __grid_constant__ CUtensorMap mapV,
       const __grid_constant__ CUtensorMap mapQ, const __grid_constant__ CUtensorMap mapO, __nv_bfloat16* __restrict__ out, unsigned ntotal, int phases) {
    extern __shared__ __align__(1024) uint8_t smem[];
    const uint32_t sb = smem_u32(smem);
    const int n = blockIdx.x, wid = __shfl_sync(0xffffffffu, threadIdx.x >> 5, 0);
    const bool spare = gridDim.x >= 68;
    if (threadIdx.x == 0) GT(1, 0);
    if (elect_one()) {
        if (wid >= 8) {
            const int i = wid - 8, h = (n >> 1) & 15, hf = n & 1;
            const uint32_t bar = sb + G_BAR + (14 + i) * 8;
            mbar_init(bar, 1);
            asm volatile("fence.proxy.async.shared::cta;" ::: "memory");
            if (n < 64 && (phases & 1)) {
                mbar_expect(bar, BLK);
                if (n < 32) tma2d(sb + (3 + i) * BLK, &mapQ, h * DH + 64 * i, 224 * hf, bar);
                else tma3d(sb + (3 + i) * BLK, &mapO, 0, h * DH + 64 * i, 7 * hf, bar);
            }
        } else {
            if (wid < 7) { mbar_init(sb + G_BAR + wid * 8, 1); mbar_init(sb + G_BAR + (7 + wid) * 8, 8); }
            asm volatile("fence.mbarrier_init.release.cluster;" ::: "memory");
            asm volatile("fence.proxy.async.shared::cta;" ::: "memory");
        }
    }
    __syncwarp();
    cluster_arrive(); cluster_wait();
    if (wid < 8) {
        asm volatile("setmaxnreg.inc.sync.aligned.u32 240;");
        if (elect_one()) {
#pragma unroll 1
            for (int i = wid; i < 47; i += 8) mbar_init(sb + G_PUB + i * 8, i < 39 ? 4 : 1);
        }
        const unsigned epoch = uni(ld_relaxed(&g_EXIT) / ntotal);
        bar_sync(5, 352);
        if (n < 64) bulk_consumer(sb, n, epoch, out, phases, spare);
        else { cluster_arrive(); if (spare && n < 68 && (phases & 2)) spare_consumer(sb, n - 64, out); }
        if (wid == 0 && elect_one()) GT(1, 5);
        cluster_wait();
    } else {
        asm volatile("setmaxnreg.dec.sync.aligned.u32 24;");
        cluster_arrive();
        unsigned epoch = 0;
        if (wid > 8) { epoch = uni(ld_relaxed(&g_EXIT) / ntotal); bar_sync(5, 352); }
        if (wid == 9 && elect_one()) red_inc(&g_EXIT);
        if (n < 64) {
            if (wid == 8) {
                if (phases & 1) {
                    const int h = (n >> 1) & 15;
                    int slot = 0; uint32_t par = 1;
#pragma unroll 1
                    for (int tile = 0; tile < 39; tile++) {
                        const CUtensorMap* map = tile >= 7 ? &mapX : (n < 32 ? &mapK : &mapV);
                        const int x0 = tile >= 7 ? 0 : h * DH, y = 64 * (tile >= 7 ? tile - 7 : tile) + 32 * (n & 1), ns = tile >= 7 ? 14 : 8;
#pragma unroll 1
                        for (int i = 0; i < ns; i++) {
                            mbar_wait(sb + G_BAR + (7 + slot) * 8, par);
                            if (elect_one()) {
                                mbar_expect(sb + G_BAR + slot * 8, 4096);
                                tma2d_pair(sb + G_RING + slot * 4096 + (n & 1) * 2048, map, x0 + 32 * i, y, sb + G_BAR + slot * 8);
                            }
                            if (++slot == NRING) { slot = 0; par ^= 1; }
                        }
                    }
                }
            } else if (wid == 9) {
                if (phases & 2) {
#pragma unroll 1
                    for (int k = 0; k < 8; k++) {
                        const int seg = k < 7 ? unit_segment(n, k, spare) : TAIL + (n >> 3);
                        if (k < 7 && seg >= TAIL) continue;
                        wait_count_warp(g_CNT + seg * 32, (epoch + 1) * 64, k < 7 ? 200 : 20);
                        fence_acq();
                        if (elect_one()) mbar_arrive(sb + G_RDY + k * 8);
                    }
                }
            } else if (phases & 1) {
#pragma unroll 1
                for (int q = wid - 10; q < 39; q += 2) {
                    mbar_wait(sb + G_PUB + q * 8, 0);
                    fence_rel();
                    if (elect_one()) {
                        st_relaxed(g_FT + n * 32 + (q & 1), epoch * 32 + (q >> 1) + 1);
                        if (q == 6) GT(1, 2);
                        if (q == 7) GT(1, 3);
                    }
                }
            }
        } else if (wid == 9 && spare && n < 68 && (phases & 2)) {
            int slot = 0; uint32_t par = 1;
#pragma unroll 1
            for (int i = n - 64; spare_segment(i) < TAIL; i += 4) {
                const int seg = spare_segment(i);
                wait_count_warp(g_CNT + seg * 32, (epoch + 1) * 64, 50);
                fence_acq();
                asm volatile("fence.proxy.async.global;" ::: "memory");
#pragma unroll 1
                for (int sh = (seg & (RS - 1)) * 16, h = 0; h < 16; h++, sh++) {
                    mbar_wait(sb + G_BAR + (7 + slot) * 8, par);
                    if (elect_one()) {
                        const uint32_t dst = sb + slot * PVS, bar = sb + G_BAR + slot * 8;
                        mbar_expect(bar, PVS);
                        bulk_g2s(dst, g_V + sh * 28672, 28672, bar); bulk_g2s(dst + PV_U, g_U + sh * 1792, 7168, bar); bulk_g2s(dst + PV_P, g_P + sh * 448, 1792, bar);
                    }
                    if (++slot == PV_N) { slot = 0; par ^= 1; }
                }
            }
        }
        cluster_wait();
    }
}

}

extern "C" void kernel_launch(void* const* d_in, const int* in_sizes, int n_in, void* d_out, int out_size) {
    typedef const __nv_bfloat16* bp;
    __nv_bfloat16* out = (__nv_bfloat16*)d_out;
    const SsmArgs ssm = {(bp)d_in[1], (bp)d_in[2], (bp)d_in[3], (bp)d_in[4], (bp)d_in[5], (bp)d_in[6]};
    const bp x = (bp)d_in[7], mem0 = (bp)d_in[8];
    static int nsm = 0;
    typedef CUresult (*EncodeFn)(CUtensorMap*, CUtensorMapDataType, cuuint32_t, void*, const cuuint64_t*, const cuuint64_t*, const cuuint32_t*,
                                 const cuuint32_t*, CUtensorMapInterleave, CUtensorMapSwizzle, CUtensorMapL2promotion, CUtensorMapFloatOOBfill);
    static EncodeFn encode = nullptr;
    if (!nsm) {
        cudaFuncSetAttribute(k_rec, cudaFuncAttributeMaxDynamicSharedMemorySize, R_SMEM);
        cudaFuncSetAttribute(k_rec, cudaFuncAttributeNonPortableClusterSizeAllowed, 1);
        cudaFuncSetAttribute(k_bulk, cudaFuncAttributeMaxDynamicSharedMemorySize, G_SMEM);
        int dev = 0; cudaGetDevice(&dev);
        cudaDeviceGetAttribute(&nsm, cudaDevAttrMultiProcessorCount, dev);
        cudaDriverEntryPointQueryResult qr;
        cudaGetDriverEntryPoint("cuTensorMapEncodeTiled", (void**)&encode, cudaEnableDefault, &qr);
    }
    auto make_map = [&](const void* p, int rank, cuuint64_t d0, cuuint64_t d1, cuuint64_t d2, cuuint64_t s1, cuuint64_t s2,
                        cuuint32_t b0, cuuint32_t b1, cuuint32_t b2, CUtensorMapSwizzle sw) {
        CUtensorMap m;
        const cuuint64_t dims[3] = {d0, d1, d2}, strides[2] = {s1, s2};
        const cuuint32_t box[3] = {b0, b1, b2}, es[3] = {1, 1, 1};
        encode(&m, CU_TENSOR_MAP_DATA_TYPE_BFLOAT16, rank, (void*)p, dims, strides, box, es, CU_TENSOR_MAP_INTERLEAVE_NONE,
               sw, CU_TENSOR_MAP_L2_PROMOTION_L2_128B, CU_TENSOR_MAP_FLOAT_OOB_FILL_NONE);
        return m;
    };
    const CUtensorMap mapX = make_map(x, 2, D, S, 1, D * 2, 0, 32, 32, 1, CU_TENSOR_MAP_SWIZZLE_64B);
    const CUtensorMap mapXs = make_map(x, 2, D, S, 1, D * 2, 0, 64, 32, 1, CU_TENSOR_MAP_SWIZZLE_128B);
    const CUtensorMap mapU = make_map(d_in[0], 2, D, S, 1, D * 2, 0, 8, 256, 1, CU_TENSOR_MAP_SWIZZLE_NONE);
    const CUtensorMap mapY = make_map(out, 2, OUTW, S, 1, OUTW * 2, 0, 8, 128, 1, CU_TENSOR_MAP_SWIZZLE_NONE);
    const CUtensorMap mapQ = make_map(d_in[9], 2, 4096, D, 1, 8192, 0, 64, 224, 1, CU_TENSOR_MAP_SWIZZLE_128B);
    const CUtensorMap mapK = make_map(d_in[10], 2, 4096, D, 1, 8192, 0, 32, 32, 1, CU_TENSOR_MAP_SWIZZLE_64B);
    const CUtensorMap mapV = make_map(d_in[11], 2, 4096, D, 1, 8192, 0, 32, 32, 1, CU_TENSOR_MAP_SWIZZLE_64B);
    const CUtensorMap mapO = make_map(d_in[12], 3, 32, 4096, 14, D * 2, 64, 32, 64, 7, CU_TENSOR_MAP_SWIZZLE_64B);
    const int nbulk = nsm >= 132 ? 68 : 64;
    k_rec<<<64, 384, R_SMEM, cudaStreamPerThread>>>(mapXs, mapU, mapY, ssm, (const uint8_t*)x, mem0, (const uint8_t*)d_in[10],
                                                    (const uint8_t*)d_in[11], (unsigned)(64 + nbulk), 0u);
    cudaLaunchAttribute pdl[1];
    pdl[0].id = cudaLaunchAttributeProgrammaticStreamSerialization;
    pdl[0].val.programmaticStreamSerializationAllowed = 1;
    cudaLaunchConfig_t cfg = {};
    cfg.stream = cudaStreamPerThread;
    cfg.attrs = pdl; cfg.numAttrs = 1;
    cfg.gridDim = dim3(nbulk); cfg.blockDim = dim3(384); cfg.dynamicSmemBytes = G_SMEM;
    cudaLaunchKernelEx(&cfg, k_bulk, mapX, mapK, mapV, mapQ, mapO, out, (unsigned)(64 + nbulk), 3);
}
```

```cpp
#include <cuda.h>
#include <cuda_runtime.h>
#include <cuda_bf16.h>
#include <cuda_fp16.h>
#include <stdint.h>
#include <string.h>

namespace {

constexpr int D = 448, S = 2048, NSEG = 64, DH = 256, NST = 256, OUTW = 896;
constexpr int RS = 16;

__device__ uint4 g_F[2 * 16 * 4 * 28 * 7 * 32];
__device__ __align__(128) uint8_t g_K[RS * 16 * 4 * 4 * 1792];
__device__ __align__(128) uint8_t g_V[RS * 16 * 56 * 512];
__device__ __align__(128) uint32_t g_P[RS * 16 * 14 * 32];
__device__ __align__(128) uint32_t g_U[RS * 16 * 56 * 32];
__device__ __align__(128) uint8_t g_ACC[98304];
__device__ unsigned g_FT[64 * 32];
__device__ unsigned g_CNT[NSEG * 32];
__device__ unsigned g_WD[32 * 32];
__device__ unsigned g_INIT, g_EXIT;
#define GT(k, i) {}

__host__ __device__ constexpr int sig0(int k) { return k == 6 ? 12 : 4 * (k >> 1) + (k & 1); }
__host__ __device__ constexpr int sig1(int k) { return k == 6 ? 13 : 4 * (k >> 1) + (k & 1) + 2; }
constexpr int SPIN = 1 << 22;

__device__ __forceinline__ uint32_t smem_u32(const void* p) { return (uint32_t)__cvta_generic_to_shared(p); }
__device__ __forceinline__ void mma16816(float* c, uint32_t a0, uint32_t a1, uint32_t a2, uint32_t a3, uint32_t b0, uint32_t b1) {
    asm volatile("mma.sync.aligned.m16n8k16.row.col.f32.bf16.bf16.f32 {%0,%1,%2,%3},{%4,%5,%6,%7},{%8,%9},{%0,%1,%2,%3};"
                 : "+f"(c[0]), "+f"(c[1]), "+f"(c[2]), "+f"(c[3]) : "r"(a0), "r"(a1), "r"(a2), "r"(a3), "r"(b0), "r"(b1));
}
__device__ __forceinline__ void mma16816z(float* c, uint32_t a0, uint32_t a1, uint32_t a2, uint32_t a3, uint32_t b0, uint32_t b1) {
    asm volatile("mma.sync.aligned.m16n8k16.row.col.f32.bf16.bf16.f32 {%0,%1,%2,%3},{%4,%5,%6,%7},{%8,%9},{%10,%10,%10,%10};"
                 : "=f"(c[0]), "=f"(c[1]), "=f"(c[2]), "=f"(c[3]) : "r"(a0), "r"(a1), "r"(a2), "r"(a3), "r"(b0), "r"(b1), "f"(0.f));
}
__device__ __forceinline__ void mma1688(float* c, uint32_t a0, uint32_t a1, uint32_t b0) {
    asm volatile("mma.sync.aligned.m16n8k8.row.col.f32.bf16.bf16.f32 {%0,%1,%2,%3},{%4,%5},{%6},{%0,%1,%2,%3};"
                 : "+f"(c[0]), "+f"(c[1]), "+f"(c[2]), "+f"(c[3]) : "r"(a0), "r"(a1), "r"(b0));
}
__device__ __forceinline__ void mmaq(float* c, const uint4& a, uint32_t b0, uint32_t b1) { mma16816(c, a.x, a.y, a.z, a.w, b0, b1); }
__device__ __forceinline__ void mmaqz(float* c, const uint4& a, uint32_t b0, uint32_t b1) { mma16816z(c, a.x, a.y, a.z, a.w, b0, b1); }
__device__ __forceinline__ uint32_t pack_bf16(float lo, float hi) {
    uint32_t r; asm("cvt.rn.bf16x2.f32 %0,%1,%2;" : "=r"(r) : "f"(hi), "f"(lo)); return r;
}
__device__ __forceinline__ uint32_t pack_bf16_again(float lo, float hi) {
    uint32_t r; asm("cvt.rn.relu.bf16x2.f32 %0,%1,%2;" : "=r"(r) : "f"(hi), "f"(lo)); return r;
}
__device__ __forceinline__ uint32_t pack_f16(float lo, float hi) {
    uint32_t r; asm("cvt.rn.f16x2.f32 %0,%1,%2;" : "=r"(r) : "f"(hi), "f"(lo)); return r;
}
__device__ __forceinline__ uint32_t prmt(uint32_t a, uint32_t b, uint32_t sel) { uint32_t r; asm("prmt.b32 %0,%1,%2,%3;" : "=r"(r) : "r"(a), "r"(b), "r"(sel)); return r; }
__device__ __forceinline__ uint32_t umin3(uint32_t a, uint32_t b, uint32_t c) { uint32_t r; asm("{.reg .u32 t; min.u32 t,%1,%3; min.u32 %0,t,%2;}" : "=r"(r) : "r"(a), "r"(b), "r"(c)); return r; }
__device__ __forceinline__ uint32_t movm(uint32_t a) {
    uint32_t d; asm volatile("movmatrix.sync.aligned.m8n8.trans.b16 %0,%1;" : "=r"(d) : "r"(a)); return d;
}
__device__ __forceinline__ void ldsm4(uint32_t* r, uint32_t a) {
    asm volatile("ldmatrix.sync.aligned.m8n8.x4.shared.b16 {%0,%1,%2,%3},[%4];" : "=r"(r[0]), "=r"(r[1]), "=r"(r[2]), "=r"(r[3]) : "r"(a) : "memory");
}
__device__ __forceinline__ uint4 ldsm4q(uint32_t a) { uint32_t r[4]; ldsm4(r, a); return make_uint4(r[0], r[1], r[2], r[3]); }
__device__ __forceinline__ void stsm4(uint32_t a, const uint4& v) {
    asm volatile("stmatrix.sync.aligned.m8n8.x4.shared.b16 [%0],{%1,%2,%3,%4};" ::"r"(a), "r"(v.x), "r"(v.y), "r"(v.z), "r"(v.w) : "memory");
}
__device__ __forceinline__ void stsm4t(uint32_t a, const uint4& v) {
    asm volatile("stmatrix.sync.aligned.m8n8.x4.trans.shared.b16 [%0],{%1,%2,%3,%4};" ::"r"(a), "r"(v.x), "r"(v.y), "r"(v.z), "r"(v.w) : "memory");
}
__device__ __forceinline__ uint4 movm4(const uint4& v) { return make_uint4(movm(v.x), movm(v.y), movm(v.z), movm(v.w)); }
__device__ __forceinline__ void stsm2(uint32_t a, uint32_t x, uint32_t y) {
    asm volatile("stmatrix.sync.aligned.m8n8.x2.shared.b16 [%0],{%1,%2};" ::"r"(a), "r"(x), "r"(y) : "memory");
}
__device__ __forceinline__ uint4 lds128(uint32_t a) {
    uint4 v; asm volatile("ld.shared.v4.u32 {%0,%1,%2,%3},[%4];" : "=r"(v.x), "=r"(v.y), "=r"(v.z), "=r"(v.w) : "r"(a) : "memory"); return v;
}
__device__ __forceinline__ float4 lds128f(uint32_t a) {
    float4 v; asm volatile("ld.shared.v4.f32 {%0,%1,%2,%3},[%4];" : "=f"(v.x), "=f"(v.y), "=f"(v.z), "=f"(v.w) : "r"(a) : "memory"); return v;
}
__device__ __forceinline__ uint2 lds64(uint32_t a) {
    uint2 v; asm volatile("ld.shared.v2.u32 {%0,%1},[%2];" : "=r"(v.x), "=r"(v.y) : "r"(a) : "memory"); return v;
}
__device__ __forceinline__ float2 lds64f(uint32_t a) {
    float2 v; asm volatile("ld.shared.v2.f32 {%0,%1},[%2];" : "=f"(v.x), "=f"(v.y) : "r"(a) : "memory"); return v;
}
__device__ __forceinline__ uint32_t lds32(uint32_t a) {
    uint32_t v; asm volatile("ld.shared.u32 %0,[%1];" : "=r"(v) : "r"(a) : "memory"); return v;
}
__device__ __forceinline__ uint32_t lds32v(uint32_t a) {
    uint32_t v; asm volatile("ld.volatile.shared.u32 %0,[%1];" : "=r"(v) : "r"(a) : "memory"); return v;
}
__device__ __forceinline__ float lds32f(uint32_t a) { return __uint_as_float(lds32(a)); }
__device__ __forceinline__ void sts128(uint32_t a, uint32_t x, uint32_t y, uint32_t z, uint32_t w) {
    asm volatile("st.shared.v4.u32 [%0],{%1,%2,%3,%4};" ::"r"(a), "r"(x), "r"(y), "r"(z), "r"(w) : "memory");
}
__device__ __forceinline__ void sts64(uint32_t a, uint32_t x, uint32_t y) {
    asm volatile("st.shared.v2.u32 [%0],{%1,%2};" ::"r"(a), "r"(x), "r"(y) : "memory");
}
__device__ __forceinline__ void sts64f(uint32_t a, float x, float y) { sts64(a, __float_as_uint(x), __float_as_uint(y)); }
__device__ __forceinline__ void sts32(uint32_t a, uint32_t x) { asm volatile("st.shared.u32 [%0],%1;" ::"r"(a), "r"(x) : "memory"); }
__device__ __forceinline__ void sts32f(uint32_t a, float x) { sts32(a, __float_as_uint(x)); }
#define ADDR3(ins) "{.reg .u32 t; add.u32 t," ins "}"
template <int I> __device__ __forceinline__ uint4 lds128u(uint32_t a, uint32_t u) {
    uint4 v; asm volatile(ADDR3("%4,%5; ld.volatile.shared.v4.u32 {%0,%1,%2,%3},[t+%6];") : "=r"(v.x), "=r"(v.y), "=r"(v.z), "=r"(v.w) : "r"(a), "r"(u), "n"(I) : "memory"); return v;
}
template <int I> __device__ __forceinline__ float4 lds128fu(uint32_t a, uint32_t u) {
    const uint4 v = lds128u<I>(a, u); return make_float4(__uint_as_float(v.x), __uint_as_float(v.y), __uint_as_float(v.z), __uint_as_float(v.w));
}
template <int I> __device__ __forceinline__ uint2 lds64u(uint32_t a, uint32_t u) {
    uint2 v; asm volatile(ADDR3("%2,%3; ld.volatile.shared.v2.u32 {%0,%1},[t+%4];") : "=r"(v.x), "=r"(v.y) : "r"(a), "r"(u), "n"(I) : "memory"); return v;
}
template <int I> __device__ __forceinline__ float2 lds64fu(uint32_t a, uint32_t u) { const uint2 v = lds64u<I>(a, u); return make_float2(__uint_as_float(v.x), __uint_as_float(v.y)); }
template <int I> __device__ __forceinline__ uint4 ldsm4u(uint32_t a, uint32_t u) {
    uint4 v; asm volatile(ADDR3("%4,%5; ldmatrix.sync.aligned.m8n8.x4.shared.b16 {%0,%1,%2,%3},[t+%6];") : "=r"(v.x), "=r"(v.y), "=r"(v.z), "=r"(v.w) : "r"(a), "r"(u), "n"(I) : "memory"); return v;
}
template <int I> __device__ __forceinline__ void ldsm4u_over(uint4& v, uint32_t a, uint32_t u, uint32_t z) {
    asm volatile("{.reg .u32 t; .reg .pred p; setp.eq.u32 p,%7,0; add.u32 t,%4,%5; @p ldmatrix.sync.aligned.m8n8.x4.shared.b16 {%0,%1,%2,%3},[t+%6];}"
                 : "+r"(v.x), "+r"(v.y), "+r"(v.z), "+r"(v.w) : "r"(a), "r"(u), "n"(I), "r"(z) : "memory");
}
template <int I> __device__ __forceinline__ uint2 ldsm2u(uint32_t a, uint32_t u) {
    uint2 v; asm volatile(ADDR3("%2,%3; ldmatrix.sync.aligned.m8n8.x2.shared.b16 {%0,%1},[t+%4];") : "=r"(v.x), "=r"(v.y) : "r"(a), "r"(u), "n"(I) : "memory"); return v;
}
template <int I> __device__ __forceinline__ void stsm4u(uint32_t a, uint32_t u, uint32_t x, uint32_t y, uint32_t z, uint32_t w) {
    asm volatile(ADDR3("%0,%1; stmatrix.sync.aligned.m8n8.x4.shared.b16 [t+%2],{%3,%4,%5,%6};") ::"r"(a), "r"(u), "n"(I), "r"(x), "r"(y), "r"(z), "r"(w) : "memory");
}
template <int I> __device__ __forceinline__ void stsm2u(uint32_t a, uint32_t u, uint32_t x, uint32_t y) {
    asm volatile(ADDR3("%0,%1; stmatrix.sync.aligned.m8n8.x2.shared.b16 [t+%2],{%3,%4};") ::"r"(a), "r"(u), "n"(I), "r"(x), "r"(y) : "memory");
}
template <int I> __device__ __forceinline__ uint4 ldsm4tu(uint32_t a, uint32_t u) {
    uint4 v; asm volatile(ADDR3("%4,%5; ldmatrix.sync.aligned.m8n8.x4.trans.shared.b16 {%0,%1,%2,%3},[t+%6];") : "=r"(v.x), "=r"(v.y), "=r"(v.z), "=r"(v.w) : "r"(a), "r"(u), "n"(I) : "memory"); return v;
}
__device__ __forceinline__ uint32_t uni(uint32_t v) { return __shfl_sync(0xffffffffu, v, 0); }
template <int I> __device__ __forceinline__ void sts128u(uint32_t a, uint32_t u, uint32_t x, uint32_t y, uint32_t z, uint32_t w) {
    asm volatile(ADDR3("%0,%1; st.shared.v4.u32 [t+%2],{%3,%4,%5,%6};") ::"r"(a), "r"(u), "n"(I), "r"(x), "r"(y), "r"(z), "r"(w) : "memory");
}
template <int I> __device__ __forceinline__ void sts64u(uint32_t a, uint32_t u, uint32_t x, uint32_t y) {
    asm volatile(ADDR3("%0,%1; st.shared.v2.u32 [t+%2],{%3,%4};") ::"r"(a), "r"(u), "n"(I), "r"(x), "r"(y) : "memory");
}
__device__ __forceinline__ uint32_t add_here(uint32_t a, uint32_t b) { uint32_t r; asm volatile("add.u32 %0,%1,%2;" : "=r"(r) : "r"(a), "r"(b)); return r; }
__device__ __forceinline__ uint8_t* add_here(uint8_t* p, uint32_t o) { uint8_t* r; asm volatile("{.reg .u64 t; cvt.u64.u32 t,%2; add.u64 %0,%1,t;}" : "=l"(r) : "l"(p), "r"(o)); return r; }
__device__ __forceinline__ uint32_t mapa(uint32_t a, uint32_t r) {
    uint32_t o; asm("mapa.shared::cluster.u32 %0,%1,%2;" : "=r"(o) : "r"(a), "r"(r)); return o;
}
__device__ __forceinline__ void st_async4(uint32_t dst, uint32_t bar, float x, float y, float z, float w) {
    asm volatile("st.async.weak.shared::cluster.mbarrier::complete_tx::bytes.v4.f32 [%0],{%1,%2,%3,%4},[%5];"
                 ::"r"(dst), "f"(x), "f"(y), "f"(z), "f"(w), "r"(bar) : "memory");
}
__device__ __forceinline__ void st_async2(uint32_t dst, uint32_t bar, float x, float y) {
    asm volatile("st.async.weak.shared::cluster.mbarrier::complete_tx::bytes.v2.f32 [%0],{%1,%2},[%3];"
                 ::"r"(dst), "f"(x), "f"(y), "r"(bar) : "memory");
}
__device__ __forceinline__ void st_async2_if(bool on, uint32_t dst, uint32_t bar, float x, float y) {
    asm volatile("{.reg .pred p; setp.ne.b32 p,%4,0; @p st.async.weak.shared::cluster.mbarrier::complete_tx::bytes.v2.f32 [%0],{%1,%2},[%3];}"
                 ::"r"(dst), "f"(x), "f"(y), "r"(bar), "r"((int)on) : "memory");
}
__device__ __forceinline__ void st_async1_if(bool on, uint32_t dst, uint32_t bar, uint32_t x) {
    asm volatile("{.reg .pred p; setp.ne.b32 p,%3,0; @p st.async.weak.shared::cluster.mbarrier::complete_tx::bytes.u32 [%0],%1,[%2];}"
                 ::"r"(dst), "r"(x), "r"(bar), "r"((int)on) : "memory");
}
__device__ __forceinline__ float ldr32f(uint32_t a) {
    float v; asm volatile("ld.shared::cluster.f32 %0,[%1];" : "=f"(v) : "r"(a) : "memory"); return v;
}
__device__ __forceinline__ void mbar_init(uint32_t bar, int cnt) { asm volatile("mbarrier.init.shared::cta.b64 [%0],%1;" ::"r"(bar), "r"(cnt) : "memory"); }
__device__ __forceinline__ void mbar_expect(uint32_t bar, int bytes) {
    asm volatile("mbarrier.arrive.expect_tx.shared::cta.b64 _,[%0],%1;" ::"r"(bar), "r"(bytes) : "memory");
}
__device__ __forceinline__ void mbar_arrive(uint32_t a) { asm volatile("mbarrier.arrive.release.cta.shared::cta.b64 _,[%0];" ::"r"(a) : "memory"); }
__device__ __forceinline__ void mbar_wait(uint32_t bar, uint32_t parity) {
    asm volatile("{.reg .pred p; .reg .u32 n; mov.u32 n,0;\n"
                 "W: mbarrier.try_wait.parity.shared::cta.b64 p,[%0],%1; @p bra D; add.u32 n,n,1; setp.lt.u32 p,n,%2; @p bra W; trap;\n"
                 "D:}" ::"r"(bar), "r"(parity), "n"(SPIN) : "memory");
}
__device__ __forceinline__ void mbar_wait_cl(uint32_t bar, uint32_t parity) {
    asm volatile("{.reg .pred p,q; .reg .u32 n; mov.u32 n,0;\n"
                 "W: add.u32 n,n,1; setp.gt.u32 q,n,%1; @q trap; mbarrier.try_wait.parity.relaxed.cluster.shared::cta.b64 p,[%0],%2; @!p bra W;\n"
                 "fence.acquire.sync_restrict::shared::cluster.cluster;}" ::"r"(bar), "n"(SPIN), "r"(parity) : "memory");
}
__device__ __forceinline__ void bulk_g2s(uint32_t dst, const void* src, int bytes, uint32_t bar) {
    asm volatile("cp.async.bulk.shared::cluster.global.mbarrier::complete_tx::bytes [%0],[%1],%2,[%3];"
                 ::"r"(dst), "l"(src), "r"(bytes), "r"(bar) : "memory");
}
__device__ __forceinline__ void tma2d(uint32_t dst, const CUtensorMap* map, int x, int y, uint32_t bar) {
    asm volatile("cp.async.bulk.tensor.2d.shared::cluster.global.mbarrier::complete_tx::bytes [%0],[%1,{%2,%3}],[%4];"
                 ::"r"(dst), "l"(map), "r"(x), "r"(y), "r"(bar) : "memory");
}
__device__ __forceinline__ void tma2d_pair(uint32_t dst, const CUtensorMap* map, int x, int y, uint32_t bar) {
    asm volatile("cp.async.bulk.tensor.2d.shared::cluster.global.mbarrier::complete_tx::bytes.multicast::cluster [%0],[%1,{%2,%3}],[%4],%5;"
                 ::"r"(dst), "l"(map), "r"(x), "r"(y), "r"(bar), "h"((uint16_t)3) : "memory");
}
__device__ __forceinline__ void tma3d(uint32_t dst, const CUtensorMap* map, int x, int y, int z, uint32_t bar) {
    asm volatile("cp.async.bulk.tensor.3d.shared::cluster.global.mbarrier::complete_tx::bytes [%0],[%1,{%2,%3,%4}],[%5];"
                 ::"r"(dst), "l"(map), "r"(x), "r"(y), "r"(z), "r"(bar) : "memory");
}
__device__ __forceinline__ void prefetch_l2(const void* p, int bytes) {
    asm volatile("cp.async.bulk.prefetch.L2.global [%0],%1;" ::"l"(p), "r"(bytes) : "memory");
}
__device__ __forceinline__ int fresh_lane() { int l; asm volatile("mov.u32 %0,%%laneid;" : "=r"(l)); return __shfl_sync(0xffffffffu, l, l); }
__device__ __forceinline__ bool elect_one() {
    uint32_t r; asm volatile("{.reg .pred p; elect.sync _|p,0xffffffff; selp.u32 %0,1,0,p;}" : "=r"(r)); return r;
}
__device__ __forceinline__ void bar_sync(int id, int n) { asm volatile("bar.sync %0,%1;" ::"r"(id), "r"(n) : "memory"); }
__device__ __forceinline__ void bar_arrive(int id, int n) { asm volatile("bar.arrive %0,%1;" ::"r"(id), "r"(n) : "memory"); }
__device__ __forceinline__ uint4 ld_relaxed4(const void* p) {
    uint4 v; asm volatile("ld.relaxed.gpu.global.v4.u32 {%0,%1,%2,%3},[%4];" : "=r"(v.x), "=r"(v.y), "=r"(v.z), "=r"(v.w) : "l"(p) : "memory"); return v;
}
__device__ __forceinline__ unsigned ld_relaxed(const unsigned* p) {
    unsigned v; asm volatile("ld.relaxed.gpu.global.u32 %0,[%1];" : "=r"(v) : "l"(p) : "memory"); return v;
}
__device__ __forceinline__ void st_relaxed(unsigned* p, unsigned v) { asm volatile("st.relaxed.gpu.global.u32 [%0],%1;" ::"l"(p), "r"(v) : "memory"); }
__device__ __forceinline__ void stg32(void* p, uint32_t v) { asm volatile("st.global.u32 [%0],%1;" ::"l"(p), "r"(v) : "memory"); }
__device__ __forceinline__ void red_inc(unsigned* p) { asm volatile("red.relaxed.gpu.global.add.u32 [%0],1;" ::"l"(p) : "memory"); }
__device__ __forceinline__ void red_add(unsigned* p, unsigned v) { asm volatile("red.relaxed.gpu.global.add.u32 [%0],%1;" ::"l"(p), "r"(v) : "memory"); }
__device__ __forceinline__ void fence_acq() { asm volatile("fence.acquire.gpu;" ::: "memory"); }
__device__ __forceinline__ void fence_rel() { asm volatile("fence.release.gpu;" ::: "memory"); }
__device__ __forceinline__ void wait_count(const unsigned* p, unsigned goal, unsigned sleep_ns) {
    int it = 0;
    while ((int)(ld_relaxed(p) - goal) < 0) { if (sleep_ns) __nanosleep(sleep_ns); if (++it > SPIN) __trap(); }
}
__device__ __forceinline__ void wait_count_warp(const unsigned* p, unsigned goal, unsigned sleep_ns) {
    int it = 0;
    while (__any_sync(0xffffffffu, (int)(ld_relaxed(p) - goal) < 0)) { if (sleep_ns) __nanosleep(sleep_ns); if (++it > SPIN) __trap(); }
}
__device__ __forceinline__ void red_bf16x8(void* p, bool on, uint32_t x, uint32_t y, uint32_t z, uint32_t w) {
    asm volatile("{.reg .pred p; setp.ne.b32 p,%5,0; @p red.relaxed.gpu.global.add.noftz.v4.bf16x2 [%0],{%1,%2,%3,%4};}"
                 ::"l"(p), "r"(x), "r"(y), "r"(z), "r"(w), "r"((int)on) : "memory");
}
__device__ __forceinline__ void mbar_arrive_if(bool on, uint32_t a) {
    asm volatile("{.reg .pred p; setp.ne.b32 p,%1,0; @p mbarrier.arrive.release.cta.shared::cta.b64 _,[%0];}" ::"r"(a), "r"((int)on) : "memory");
}
__device__ __forceinline__ void mbar_arrive_cl_if(bool on, uint32_t a) {
    asm volatile("{.reg .pred p; setp.ne.b32 p,%1,0; @p mbarrier.arrive.relaxed.cluster.shared::cluster.b64 _,[%0];}" ::"r"(a), "r"((int)on) : "memory");
}
__device__ __forceinline__ uint32_t any_reg() { uint32_t r; asm volatile("" : "=r"(r)); return r; }
__device__ __forceinline__ float ex2(float x) { float y; asm("ex2.approx.ftz.f32 %0,%1;" : "=f"(y) : "f"(x)); return y; }
__device__ __forceinline__ float rcp(float x) { float y; asm("rcp.approx.ftz.f32 %0,%1;" : "=f"(y) : "f"(x)); return y; }
__device__ __forceinline__ uint32_t clk() {
    uint32_t c; asm volatile("{.reg .u64 t; .reg .u32 h; mov.u64 t,%%clock64; mov.b64 {%0,h},t;}" : "=r"(c)::"memory"); return c;
}
__device__ __forceinline__ uint32_t hadd_bf(uint32_t a, uint32_t b) { uint32_t r; asm("add.rn.bf16x2 %0,%1,%2;" : "=r"(r) : "r"(a), "r"(b)); return r; }
__device__ __forceinline__ uint32_t hmul_bf(uint32_t a, uint32_t b) { uint32_t r; asm("mul.rn.bf16x2 %0,%1,%2;" : "=r"(r) : "r"(a), "r"(b)); return r; }
__device__ __forceinline__ uint32_t hsum4(uint32_t a, uint32_t b, uint32_t c, uint32_t d) { return hadd_bf(hadd_bf(a, b), hadd_bf(c, d)); }
__device__ __forceinline__ uint32_t amax_bf(uint32_t a, uint32_t b) { uint32_t r; asm("max.xorsign.abs.bf16x2 %0,%1,%2;" : "=r"(r) : "r"(a), "r"(b)); return r; }
__device__ __forceinline__ float4 sum4(float4 a, float4 b, float4 c, float4 d) {
    return make_float4((a.x + b.x) + (c.x + d.x), (a.y + b.y) + (c.y + d.y), (a.z + b.z) + (c.z + d.z), (a.w + b.w) + (c.w + d.w));
}
__device__ __forceinline__ void cluster_arrive() { asm volatile("barrier.cluster.arrive.relaxed.aligned;" ::: "memory"); }
__device__ __forceinline__ void cluster_arrive_rel() { asm volatile("barrier.cluster.arrive.release.aligned;" ::: "memory"); }
__device__ __forceinline__ void cluster_wait() { asm volatile("barrier.cluster.wait.aligned;" ::: "memory"); }
#define SCHED_FENCE(z, k) do { if ((z) == (k)) __trap(); } while (0)

template <int TB>
__device__ __forceinline__ void wgmma224(float* d, uint64_t da, uint64_t db, int accumulate) {
    asm volatile("{.reg .pred p; setp.ne.b32 p,%114,0;\n"
                 "wgmma.mma_async.sync.aligned.m64n224k16.f32.bf16.bf16 {%0,%1,%2,%3,%4,%5,%6,%7,%8,%9,%10,%11,%12,%13,%14,%15,%16,%17,%18,%19,%20,%21,%22,%23,%24,%25,%26,%27,%28,%29,%30,%31,%32,%33,%34,%35,%36,%37,%38,%39,%40,%41,%42,%43,%44,%45,%46,%47,%48,%49,%50,%51,%52,%53,%54,%55,%56,%57,%58,%59,%60,%61,%62,%63,%64,%65,%66,%67,%68,%69,%70,%71,%72,%73,%74,%75,%76,%77,%78,%79,%80,%81,%82,%83,%84,%85,%86,%87,%88,%89,%90,%91,%92,%93,%94,%95,%96,%97,%98,%99,%100,%101,%102,%103,%104,%105,%106,%107,%108,%109,%110,%111},%112,%113,p,1,1,0,%115;}"
                 : "+f"(d[0]), "+f"(d[1]), "+f"(d[2]), "+f"(d[3]), "+f"(d[4]), "+f"(d[5]), "+f"(d[6]), "+f"(d[7]), "+f"(d[8]), "+f"(d[9]), "+f"(d[10]), "+f"(d[11]), "+f"(d[12]), "+f"(d[13]), "+f"(d[14]), "+f"(d[15]), "+f"(d[16]), "+f"(d[17]), "+f"(d[18]), "+f"(d[19]), "+f"(d[20]), "+f"(d[21]), "+f"(d[22]), "+f"(d[23]), "+f"(d[24]), "+f"(d[25]), "+f"(d[26]), "+f"(d[27]), "+f"(d[28]), "+f"(d[29]), "+f"(d[30]), "+f"(d[31]), "+f"(d[32]), "+f"(d[33]), "+f"(d[34]), "+f"(d[35]), "+f"(d[36]), "+f"(d[37]), "+f"(d[38]), "+f"(d[39]), "+f"(d[40]), "+f"(d[41]), "+f"(d[42]), "+f"(d[43]), "+f"(d[44]), "+f"(d[45]), "+f"(d[46]), "+f"(d[47]), "+f"(d[48]), "+f"(d[49]), "+f"(d[50]), "+f"(d[51]), "+f"(d[52]), "+f"(d[53]), "+f"(d[54]), "+f"(d[55]), "+f"(d[56]), "+f"(d[57]), "+f"(d[58]), "+f"(d[59]), "+f"(d[60]), "+f"(d[61]), "+f"(d[62]), "+f"(d[63]), "+f"(d[64]), "+f"(d[65]), "+f"(d[66]), "+f"(d[67]), "+f"(d[68]), "+f"(d[69]), "+f"(d[70]), "+f"(d[71]), "+f"(d[72]), "+f"(d[73]), "+f"(d[74]), "+f"(d[75]), "+f"(d[76]), "+f"(d[77]), "+f"(d[78]), "+f"(d[79]), "+f"(d[80]), "+f"(d[81]), "+f"(d[82]), "+f"(d[83]), "+f"(d[84]), "+f"(d[85]), "+f"(d[86]), "+f"(d[87]), "+f"(d[88]), "+f"(d[89]), "+f"(d[90]), "+f"(d[91]), "+f"(d[92]), "+f"(d[93]), "+f"(d[94]), "+f"(d[95]), "+f"(d[96]), "+f"(d[97]), "+f"(d[98]), "+f"(d[99]), "+f"(d[100]), "+f"(d[101]), "+f"(d[102]), "+f"(d[103]), "+f"(d[104]), "+f"(d[105]), "+f"(d[106]), "+f"(d[107]), "+f"(d[108]), "+f"(d[109]), "+f"(d[110]), "+f"(d[111])
                 : "l"(da), "l"(db), "r"(accumulate), "n"(TB));
}
__device__ __forceinline__ void wgmma64(float* d, uint64_t da, uint64_t db, int accumulate) {
    asm volatile("{.reg .pred p; setp.ne.b32 p,%34,0;\n"
                 "wgmma.mma_async.sync.aligned.m64n64k16.f32.bf16.bf16 {%0,%1,%2,%3,%4,%5,%6,%7,%8,%9,%10,%11,%12,%13,%14,%15,%16,%17,%18,%19,%20,%21,%22,%23,%24,%25,%26,%27,%28,%29,%30,%31},%32,%33,p,1,1,0,0;}"
                 : "+f"(d[0]), "+f"(d[1]), "+f"(d[2]), "+f"(d[3]), "+f"(d[4]), "+f"(d[5]), "+f"(d[6]), "+f"(d[7]), "+f"(d[8]), "+f"(d[9]), "+f"(d[10]), "+f"(d[11]), "+f"(d[12]), "+f"(d[13]), "+f"(d[14]), "+f"(d[15]), "+f"(d[16]), "+f"(d[17]), "+f"(d[18]), "+f"(d[19]), "+f"(d[20]), "+f"(d[21]), "+f"(d[22]), "+f"(d[23]), "+f"(d[24]), "+f"(d[25]), "+f"(d[26]), "+f"(d[27]), "+f"(d[28]), "+f"(d[29]), "+f"(d[30]), "+f"(d[31])
                 : "l"(da), "l"(db), "r"(accumulate));
}
__device__ __forceinline__ uint64_t sdesc(uint32_t addr, uint32_t lbo, uint32_t sbo, uint64_t swizzle) {
    return (uint64_t)((addr & 0x3FFFF) >> 4) | ((uint64_t)(lbo >> 4) << 16) | ((uint64_t)(sbo >> 4) << 32) | (swizzle << 62);
}
__device__ __forceinline__ void wg_fence() { asm volatile("wgmma.fence.sync.aligned;" ::: "memory"); }
__device__ __forceinline__ void wg_commit() { asm volatile("wgmma.commit_group.sync.aligned;" ::: "memory"); }
template <int N> __device__ __forceinline__ void wg_wait() { asm volatile("wgmma.wait_group.sync.aligned %0;" ::"n"(N) : "memory"); }
constexpr float LOG2E = 1.4426950408889634f;
constexpr uint32_t ONE2 = 0x3f803f80u;
constexpr uint32_t CNT16 = 0x41800000u;
constexpr uint32_t SAFE_LO = (127u - 40u) << 23, SAFE_SPAN = 80u << 23;

constexpr int C_IO = 0;
constexpr int C_UP = 2176, C_UW = 2 * C_UP + 16;
constexpr int C_U = C_IO + 32768;
constexpr int C_RN = 16, C_RX = 576, C_RM = 624, C_RF = C_RM + 4 * 64, C_RW = C_RF + 2 * 80;
constexpr int C_R = C_U + 8 * C_UW;
constexpr int C_TW = 56 * 144;
constexpr int C_T = C_R + 8 * C_RW * 4;
constexpr int C_END = C_T + 8 * C_TW;

struct SsmArgs { const __nv_bfloat16 *lar, *aim, *cre, *cim, *ldt, *dsk; };
struct cpx { float r, i; };
__device__ __forceinline__ cpx csq(cpx a) { return {fmaf(a.r, a.r, -a.i * a.i), (a.r + a.r) * a.i}; }
__device__ __forceinline__ cpx cexp(float er, float wi, float p) { const float e = ex2(er * p), x = wi * p; return {e * __cosf(x), e * __sinf(x)}; }
struct hfac { uint32_t v, s; };
__device__ __forceinline__ hfac hfactor(cpx a) { return {pack_f16(a.r, a.i), pack_f16(-a.i, a.r)}; }
__device__ __forceinline__ uint32_t hcmul(uint32_t a, hfac b) {
    uint32_t r;
    asm("{.reg .f16 l,h; .reg .b32 x,y; mov.b32 {l,h},%1; mov.b32 x,{l,l}; mov.b32 y,{h,h}; mul.rn.f16x2 x,x,%2; fma.rn.f16x2 %0,y,%3,x;}" : "=r"(r) : "r"(a), "r"(b.v), "r"(b.s));
    return r;
}
__device__ __forceinline__ void mmah(float* c, const uint4& a, uint32_t b0, uint32_t b1) {
    asm volatile("mma.sync.aligned.m16n8k16.row.col.f32.f16.f16.f32 {%0,%1,%2,%3},{%4,%5,%6,%7},{%8,%9},{%0,%1,%2,%3};"
                 : "+f"(c[0]), "+f"(c[1]), "+f"(c[2]), "+f"(c[3]) : "r"(a.x), "r"(a.y), "r"(a.z), "r"(a.w), "r"(b0), "r"(b1));
}

__device__ __forceinline__ void ssm_kernel_values(uint32_t tb, uint32_t rb, int d, int lane, const SsmArgs& p) {
    const int g = lane >> 2, t = lane & 3;
    const float dt = __bfloat162float(__float2bfloat16(expf(__bfloat162float(p.ldt[d]))));
    float up;
    {
        const uint4 a = __ldg((const uint4*)(p.lar + d * NST) + lane), b = __ldg((const uint4*)(p.aim + d * NST) + lane);
        const uint4 v = __ldg((const uint4*)(p.cre + d * NST) + lane), z = __ldg((const uint4*)(p.cim + d * NST) + lane);
        sts128(rb + lane * 16, a.x, a.y, a.z, a.w); sts128(rb + 512 + lane * 16, b.x, b.y, b.z, b.w);
        sts128(rb + 1024 + lane * 16, v.x, v.y, v.z, v.w); sts128(rb + 1536 + lane * 16, z.x, z.y, z.z, z.w);
        const uint32_t m = amax_bf(amax_bf(amax_bf(v.x, v.y), amax_bf(v.z, v.w)), amax_bf(amax_bf(z.x, z.y), amax_bf(z.z, z.w)));
        const int e = __reduce_max_sync(0xffffffffu, max(m & 0x7f800000u, (m << 16) & 0x7f800000u)) >> 23;
        up = __uint_as_float((uint32_t)min(267 - e, 253) << 23);
    }
    float acc[2][3][4];
#pragma unroll
    for (int i = 0; i < 24; i++) (&acc[0][0][0])[i] = 0.f;
    const uint32_t wa = tb + lane * 4;
    const uint32_t la_ = tb + (lane & 15) * 144 + (lane >> 4) * 16, lb_ = tb + (32 + (lane & 7)) * 144 + (lane >> 3) * 16;
    sts32(wa, 0x00003c00u); sts32(wa + 53 * 144, 0u); sts32(wa + 54 * 144, 0u); sts32(wa + 55 * 144, 0u);
    auto par = [&](int o) { uint32_t k; asm volatile("{.reg .u16 h; ld.shared.u16 h,[%1]; cvt.u32.u16 %0,h;}" : "=r"(k) : "r"(rb + lane * 2 + o) : "memory"); return k; };
    __syncwarp();
    uint32_t la = par(0), ai = par(512), cr = par(1024), ci = par(1536);
#pragma unroll 1
    for (int it = 1; it <= 8; it++) {
        __syncwarp();
        const float er = (-__bfloat162float(__float2bfloat16(expf(__uint_as_float(la << 16)))) * dt) * LOG2E;
        const float wi = __uint_as_float(ai << 16) * dt;
        uint32_t x[21], y[32];
        x[0] = pack_f16(__uint_as_float(cr << 16) * up, __uint_as_float(ci << 16) * -up);
        la = par(64 * it); ai = par(512 + 64 * it); cr = par(1024 + 64 * it); ci = par(1536 + 64 * it);
        const cpx c1 = cexp(er, wi, 1.f), w8 = cexp(er, wi, 8.f), w64 = cexp(er, wi, 64.f), c256 = cexp(er, wi, 256.f);
        const cpx w1 = {c1.r, -c1.i}, w2 = csq(w1), w16 = csq(w8), w256 = {c256.r, -c256.i}, w512 = csq(w256);
        const hfac h1 = hfactor(w1), h2 = hfactor(w2), h4 = hfactor(csq(w2)), h256 = hfactor(w256), h512 = hfactor(w512), h1024 = hfactor(csq(w512));
        const hfac f[4] = {hfactor(w16), hfactor(csq(w16)), hfactor(w64), hfactor(csq(w64))};
        x[1] = hcmul(x[0], h1); x[2] = hcmul(x[0], h2); x[3] = hcmul(x[1], h2);
#pragma unroll
        for (int k = 0; k < 4; k++) x[4 + k] = hcmul(x[k], h4);
#pragma unroll
        for (int k = 0; k < 4; k++) x[8 + k] = hcmul(x[2 * k], h256);
        x[12] = hcmul(x[0], h512); x[13] = hcmul(x[4], h512); x[14] = hcmul(x[8], h512); x[15] = hcmul(x[10], h512);
        x[16] = hcmul(x[0], h1024); x[17] = hcmul(x[8], h1024); x[18] = hcmul(x[12], h1024); x[19] = hcmul(x[14], h1024); x[20] = hcmul(x[16], h1024);
        y[0] = 0; y[1] = pack_f16(w8.r, w8.i);
#pragma unroll
        for (int k = 2; k < 32; k++) {
            const int l = k < 4 ? 0 : (k < 8 ? 1 : (k < 16 ? 2 : 3));
            y[k] = k == (2 << l) ? f[l].v : hcmul(y[k - (2 << l)], f[l]);
        }
#pragma unroll
        for (int k = 0; k < 21; k++) sts32(wa + (32 + k) * 144, x[k]);
#pragma unroll
        for (int k = 1; k < 32; k++) sts32(wa + k * 144, y[k]);
        __syncwarp();
#pragma unroll
        for (int kp = 0; kp < 2; kp++) {
            const uint4 b0 = ldsm4q(lb_ + kp * 64), b1 = ldsm4q(lb_ + 8 * 144 + kp * 64), b2 = ldsm4q(lb_ + 16 * 144 + kp * 64);
#pragma unroll
            for (int m = 0; m < 2; m++) {
                const uint4 a0 = ldsm4q(la_ + m * 16 * 144 + kp * 64), a1 = ldsm4q(la_ + m * 16 * 144 + kp * 64 + 32);
                mmah(acc[m][0], a0, b0.x, b0.y); mmah(acc[m][1], a0, b1.x, b1.y); mmah(acc[m][2], a0, b2.x, b2.y);
                mmah(acc[m][0], a1, b0.z, b0.w); mmah(acc[m][1], a1, b1.z, b1.w); mmah(acc[m][2], a1, b2.z, b2.w);
            }
        }
    }
    __syncwarp();
    const float down = __uint_as_float((254u << 23) - __float_as_uint(up)), dt2 = 2.f * dt;
    auto put16 = [&](int pos, float v) { asm volatile("st.shared.u16 [%0],%1;" ::"r"(tb + pos * 2), "h"(__bfloat16_as_ushort(__float2bfloat16(v * dt2 * down))) : "memory"); };
    auto get16 = [&](int pos) { uint32_t k; asm volatile("{.reg .u16 h; ld.shared.u16 h,[%1]; cvt.u32.u16 %0,h;}" : "=r"(k) : "r"(tb + pos * 2) : "memory"); return k; };
    const int o1 = t < 2 ? 256 + 4 * t : 256 * t, s1 = t < 2 ? 2 : 4;
#pragma unroll
    for (int m = 0; m < 2; m++)
#pragma unroll
        for (int e = 0; e < 4; e++) {
            const int b = 128 * m + 8 * g + 64 * (e >> 1);
            put16(b + 2 * t + (e & 1), acc[m][0][e]); put16(b + o1 + s1 * (e & 1), acc[m][1][e]);
            put16(b + 1024 + 512 * t + 256 * (e & 1), acc[m][2][e]);
        }
    __syncwarp();
    constexpr int NIL = 3064;
    uint32_t r[31];
    auto pos = [&](int j, int o) {
        const int y = lane + 32 * j - C_RN - o, z = lane - o, rz = (z + ((z >> 1) & 1)) & ~1;
        if (j == 0) return y < 0 ? NIL : y;
        if (j < 8) return y;
        if (j == 8) return y < 256 ? y : rz + 32 * j - C_RN;
        if (j < 16) return rz + 32 * j - C_RN;
        return y < 512 ? rz + 32 * j - C_RN : (y <= 514 ? 512 : NIL);
    };
#pragma unroll
    for (int j = 0; j < 17; j++) r[j] = get16(pos(j, 0)) | (get16(pos(j, 1)) << 16);
    const uint32_t k1024 = get16(1024);
    r[17] = (lane == 19 || lane == 20 ? k1024 : 0u) | (lane == 20 || lane == 21 ? k1024 << 16 : 0u);
#pragma unroll
    for (int j = 0; j < 8; j++) {
        const int q = lane + 32 * (j & 1) + 16, o = 4 * (j >> 1) + 4;
        r[18 + j] = get16(q >= 32 && q < 64 ? 16 * q + o : NIL) | (get16(q >= 33 && q < 65 ? 16 * q - 16 + o : NIL) << 16);
    }
#pragma unroll
    for (int j = 0; j < 5; j++) {
        const int i = lane + 32 * j, hi = i >= 80, q = i - 80 * hi + 48, o = 8 * hi + 8;
        r[26 + j] = get16(q >= 64 ? 16 * q + o : NIL) | (get16(q >= 65 ? 16 * q - 16 + o : NIL) << 16);
    }
    const uint32_t ro = rb + lane * 4;
#pragma unroll
    for (int j = 0; j < 17; j++) sts32(ro + j * 128, r[j]);
    sts32(ro + 17 * 128, 0u); sts32(ro + C_RX * 4, r[17]); sts32(rb + (C_RX + 32 + (lane & 15)) * 4, 0u);
#pragma unroll
    for (int j = 0; j < 13; j++) sts32(ro + C_RM * 4 + j * 128, r[18 + j]);
}

template <int E0, int NE, int NK>
__device__ __forceinline__ void ssm_grouped(float (&acc)[16][4], uint32_t ub, uint32_t ta, int off, int width, int lane, uint32_t zero) {
    const int g = lane >> 2, t = lane & 3, mi = lane >> 3;
    const bool sh = off >= 8;
    const uint32_t ua = ub + ((mi ^ sh) & 1) * C_UP + (8 + (lane & 7) + ((mi + sh) >> 1) - 1 - sh) * 16;
    uint32_t band[5];
#pragma unroll
    for (int i = 0; i < 5; i++) {
        const int z = g - 2 * t + 8 - 8 * i + (sh ? 24 : 16) - off;
        band[i] = ((unsigned)z < (unsigned)width ? 0x3f80u : 0u) | ((unsigned)(z - 1) < (unsigned)width ? 0x3f800000u : 0u);
    }
    const uint4 q0 = make_uint4(band[1], band[0], band[2], band[1] ^ zero), q1 = make_uint4(band[3], band[2] ^ zero, band[4], band[3] ^ zero);
    uint32_t tp[NE][2];
#pragma unroll
    for (int e = 0; e < NE; e++) { tp[e][0] = lds32(ta + (8 * e + 16) * 4); tp[e][1] = lds32v(ta + (8 * e + 8) * 4); }
#pragma unroll
    for (int k = 0; k < NK; k++) {
        float w0[4], w1[4];
        const uint4 u0 = ldsm4q(ua + k * 256), u1 = ldsm4q(ua + k * 256 + 128);
        mmaqz(w0, q0, u0.x, u0.y); mmaqz(w1, q0, u1.x, u1.y);
        mmaq(w0, q1, u0.z, u0.w); mmaq(w1, q1, u1.z, u1.w);
        const uint4 a = make_uint4(pack_bf16(w0[0], w0[1]), pack_bf16(w0[2], w0[3]), pack_bf16(w1[0], w1[1]), pack_bf16(w1[2], w1[3]));
#pragma unroll
        for (int e = 0; e < NE; e++) if (2 * k + E0 + e < 16) mmaq(acc[2 * k + E0 + e], a, tp[e][0], tp[e][1]);
    }
}

__device__ __forceinline__ void ssm_unit(uint32_t sb, uint32_t bar, uint32_t par, bool init, int d0, const SsmArgs& p, const CUtensorMap* mapU, int barid, uint32_t zero) {
    const int lane = fresh_lane(), ch = __shfl_sync(0xffffffffu, threadIdx.x >> 5, 0);
    const int g = lane >> 2, t = lane & 3, mi = lane >> 3;
    if (ch == 0 && elect_one()) {
        if (init) { mbar_init(bar, 1); asm volatile("fence.proxy.async.shared::cta;" ::: "memory"); }
        mbar_expect(bar, 32768);
#pragma unroll 1
        for (int i = 0; i < 8; i++) tma2d(sb + C_IO + i * 4096, mapU, d0, 256 * i, bar);
    }
    const uint32_t ub = sb + C_U + ch * C_UW, rb = sb + C_R + ch * C_RW * 4;
    if (lane < 16) sts128(ub + (lane >> 3) * C_UP + (lane & 7) * 16, 0u, 0u, 0u, 0u);
    const uint32_t dk = __bfloat16_as_ushort(p.dsk[d0 + ch]);
    ssm_kernel_values(sb + C_T + ch * C_TW, rb, d0 + ch, lane, p);
    if (ch == 0 && elect_one()) GT(0, 8);
    const uint32_t ioa = sb + C_IO + ch * 4096 + lane * 16, pla = sb + C_U + (lane & 7) * C_UW + (mi & 1) * C_UP + (8 + 16 * ch + (mi >> 1)) * 16;
    if (init) bar_sync(barid, 256);
    mbar_wait(bar, par);
#pragma unroll
    for (int i = 0; i < 8; i++) stsm4t(pla + i * 32, ldsm4q(ioa + i * 512));
    bar_sync(barid, 256);
    float acc[16][4];
    const uint32_t ua = ub + (mi & 1) * C_UP + (8 + 8 * (mi >> 1) + (lane & 7)) * 16, ra = rb + (C_RN + g - 2 * t) * 4;
    {
        const uint32_t dg = (g == 2 * t ? dk : 0u) | (g == 2 * t + 1 ? dk << 16 : 0u);
        const uint4 q = make_uint4(dg, dg & zero, dk & zero, dg ^ zero);
#pragma unroll
        for (int j = 0; j < 8; j++) { const uint4 b = ldsm4q(ua + j * 256); mmaqz(acc[2 * j], q, b.x, b.y); mmaqz(acc[2 * j + 1], q, b.z, b.w); }
    }
#pragma unroll 1
    for (int rho = 0; rho < 8; rho++) {
        uint32_t b[16][2];
#pragma unroll
        for (int j = 0; j < 8; j++) { const uint4 v = ldsm4q(ua + j * 256 - rho * 16); b[2 * j][0] = v.x; b[2 * j][1] = v.y; b[2 * j + 1][0] = v.z; b[2 * j + 1][1] = v.w; }
        auto diag = [&](uint32_t a, int i) {
            const uint4 q = make_uint4(lds32(a), lds32(a + 32), lds32(a - 32), lds32v(a));
#pragma unroll
            for (int j = i; j < 16; j++) mmaq(acc[j], q, b[j - i][0], b[j - i][1]);
        };
#pragma unroll
        for (int i = 0; i < 4; i++) diag(ra + rho * 64 + i * 512, i);
        if (rho < 2) { diag(ra + rho * 64 + 2048, 4); diag(ra + rho * 64 + C_RX * 4, 8); }
    }
    const uint32_t ta = rb + (g - 2 * t) * 4;
#pragma unroll 1
    for (int ph = 0; ph < 4; ph++) ssm_grouped<4, 6, 6>(acc, ub, ta + (C_RM + 64 * ph) * 4, 4 * ph + 3 - (ph & 1), 3 + 2 * (ph & 1), lane, zero);
#pragma unroll 1
    for (int ph = 0; ph < 2; ph++) ssm_grouped<8, 8, 4>(acc, ub, ta + (C_RF + 80 * ph) * 4, 5 + 7 * ph, 7 + 2 * ph, lane, zero);
    if (ch == 0 && elect_one()) GT(0, 9);
    __syncwarp();
#pragma unroll
    for (int j = 0; j < 8; j++)
        stsm4t(ua + j * 256, make_uint4(pack_bf16(acc[2 * j][0], acc[2 * j][1]), pack_bf16(acc[2 * j][2], acc[2 * j][3]),
                                        pack_bf16(acc[2 * j + 1][0], acc[2 * j + 1][1]), pack_bf16(acc[2 * j + 1][2], acc[2 * j + 1][3])));
    bar_sync(barid, 256);
#pragma unroll
    for (int i = 0; i < 8; i++) stsm4t(ioa + i * 512, ldsm4q(pla + i * 32));
    asm volatile("fence.proxy.async.shared::cta;" ::: "memory");
}
__device__ __forceinline__ void ssm_store(uint32_t sb, int d0, int i, const CUtensorMap* mapY) {
    asm volatile("cp.async.bulk.tensor.2d.global.shared::cta.bulk_group [%0,{%1,%2}],[%3];" ::"l"(mapY), "r"(d0), "r"(128 * i), "r"(sb + C_IO + i * 2048) : "memory");
    asm volatile("cp.async.bulk.commit_group;" ::: "memory");
}

#define UW0 4
#define PF2 0
#define UPIN 2
#define USTAG 1
#define SPLITMB 0
#define XFENCE 0
#define EXP_MIN 0
#define URES 3
#define VEARLY 2
#define GFIRST 0
#define WAVE2 0
#define GATE2 1
#define KLATE (WAVE2 != 0)
#define GO_DEP 8
#define POLL_DELAY 450
constexpr int S_X = 0, S_V = 8192, S_KO = 15360, S_KS = 22528, S_TB = 29696, S_ONE = 36864, STGB = 37888;
constexpr int R_STG = C_U;
constexpr int R_WB = R_STG + 3 * STGB, WB = 7680;
constexpr int W_W0 = 0;
constexpr int W_MB = 3584, W_SMI = 5632;
constexpr int W_UP = 3584, W_QRT = 5376;
constexpr int W_TAB = 4 * WB + 5632;
constexpr int R_SMM = R_WB + 8 * WB;
constexpr int R_LS = R_SMM + 4096;
constexpr int R_ALIAS_END = R_LS + 10240;
constexpr int R_MISC = (R_ALIAS_END > C_END ? R_ALIAS_END : C_END);
constexpr int R_BAR = R_MISC + 16;
constexpr int B_KV = 0, B_SM = 512, B_LS = 1024, B_H = 1536, B_PUB = 2048, B_Z = 2560;
constexpr int R_SMEM = R_BAR + 3072;
static_assert(R_SMEM <= 232448, "smem");
enum { BR_TT = 0, BR_SM = 1, BR_UP = 2, BR_RED = 3, BR_MB = 4, BR_POLL = 8, BR_GO = 12,
       BR_PRO = 0, BR_ALL = 1, BR_H = 2 };

#define DBG(i)

__device__ __forceinline__ uint32_t acc_off(int c, int q, int lane) {
    return (lane & 7) * 16 + ((lane >> 3) & 1) * 256 + (lane >> 4) * 1024 + (q & 1) * 2048 + (q >> 1) * 16384 + c * 4096;
}
__device__ __forceinline__ int tile_of(int q, int i) { return i == 3 ? 3 + 8 * (q >> 1) : (q == 3 && i == 2 ? 7 : 4 * q + i); }
__device__ __forceinline__ uint32_t acc_slot(int s) { return (s & 1) * 128 + (s & 2) * 256 + (s & 4) * 8192; }

__global__ void __cluster_dims__(4, 1, 1) __launch_bounds__(384, 1)
k_rec(const __grid_constant__ CUtensorMap mapXs, const __grid_constant__ CUtensorMap mapU, const __grid_constant__ CUtensorMap mapY, const SsmArgs ssm, const uint8_t* x, const __nv_bfloat16* __restrict__ mem0,
      const uint8_t* wk, const uint8_t* wv, unsigned ntotal, const uint32_t zero) {
    extern __shared__ __align__(1024) uint8_t smem[];
    const uint32_t sb = smem_u32(smem);
    const int tid = threadIdx.x, wid = __shfl_sync(0xffffffffu, tid >> 5, 0), w = wid & 3;
    const int bid = blockIdx.x;
    const int h = bid >> 2, c = bid & 3;
    uint8_t* const accb = (uint8_t*)(((uintptr_t)g_ACC + 32767) & ~(uintptr_t)32767);

    asm volatile("griddepcontrol.launch_dependents;" ::: "memory");
    if (wid == 0 && elect_one()) GT(0, 0);

    if (wid < 8) {
        asm volatile("setmaxnreg.inc.sync.aligned.u32 232;");
        cluster_arrive();
        if (bid < D / 8) ssm_unit(sb, sb + R_MISC + 8, 0, true, bid * 8, ssm, &mapU, BR_PRO, zero);
        asm volatile("fence.proxy.async.shared::cta;" ::: "memory");
        if (wid == 0 && elect_one()) GT(0, 1);
        bar_sync(BR_ALL, 288);
        auto load_weights = [&](uint4 (&wr)[7][6], int lane) {
            wait_count_warp(g_FT + ((wid >> 2) * 32 + 2 * h + (c >> 1)) * 32 + (lane & 1), lds32(sb + R_MISC) * 32 + min(w + 1, 4 - (lane & 1)), 40);
            fence_acq();
            const uint4* fp = g_F + ((((wid >> 2) * 16 + h) * 4 + c) * 28 + 7 * w) * 224 + lane;
            uint4 w0[7];
#pragma unroll
            for (int m = 0; m < 7; m++) w0[m] = __ldcg(fp + m * 32);
#pragma unroll
            for (int k = 0; k < 6; k++)
#pragma unroll
                for (int m = 0; m < 7; m++) wr[m][k] = __ldcg(fp + (k + 1) * 224 + m * 32);
#pragma unroll
            for (int m = 0; m < 7; m++) { const uint4 v = movm4(w0[m]); sts128(sb + R_WB + wid * WB + lane * 16 + m * 512, v.x, v.y, v.z, v.w); }
#pragma unroll
            for (int k = 0; k < 6; k++)
#pragma unroll
                for (int m = 0; m < 7; m++) wr[m][k] = movm4(wr[m][k]);
            if (wid < 3) sts128(sb + R_STG + w * STGB + S_ONE + lane * 16, ONE2, ONE2, ONE2, ONE2);
            if (wid == 4) sts128(sb + R_WB + 4 * WB + W_QRT, 0x3e803e80u, 0x3e803e80u, 0x3e803e80u, 0x3e803e80u);
            cluster_wait();
        };
        if (wid < 4) {
            asm volatile("setmaxnreg.inc.sync.aligned.u32 248;");
            const int lane = fresh_lane(), g = lane >> 2;
            const uint32_t l16 = sb + lane * 16, l8 = sb + lane * 8;
            const uint32_t zr = lane & zero;
            uint4 wr[7][6];
            load_weights(wr, lane);
            const uint32_t uw = uni(R_WB + w * WB), uc = uni(R_WB + c * WB), u2 = uni((tile_of(w, 2) - 4 * w) * 128);
            const uint32_t upoll = uni(acc_off(w, 0, 0)), ured = uni(acc_off(c, w, 0)), uk = uni(S_KO + w * 1792), uv = uni(S_V + 4 * w * 512);
            const int src = 16 * (w & 1) + (lane >> 1);
            const uint32_t sia = sb + R_WB + W_SMI + (w >> 1) * 256 + src * 8, lo = acc_off(0, 0, lane);
            uint32_t lp = sb + (lane & 7) * 16 + (lane >> 4) * 128 + ((lane >> 3) & 1) * 256;
            {
                const uint32_t ua = sb + R_WB + (4 + (lane >> 3)) * WB + W_UP + (lane & 7) * 16 + 4 * w * 128;
                const uint32_t ma = sb + R_SMM + (w < 2 ? c * 256 + src * 8 : 1024 + c * 128 + src * 4), r = (lane & 1);
                sts128u<W_TAB>(l16, uw, mapa(ma, r), mapa(sb + R_BAR + B_SM, r), mapa(ma, r + 2), mapa(sb + R_BAR + B_SM, r + 2));
                sts128u<W_TAB + 512>(l16, uw, l8 + (((g ^ w) & 1) ? S_ONE : S_V + tile_of(w, 3) * 512), ua,
                                     ((lane ^ w) & 1) ? sb + R_WB + 4 * WB + W_QRT : ua + (tile_of(w, 3) - 4 * w) * 128, lp);
            }
            const bool wodd = w & 1;
            const uint32_t ugo = uni(BR_GO + w);
            uint32_t t0 = clk() - POLL_DELAY, stg = uni(R_STG);
            uint4 ub = make_uint4(0, 0, 0, 0), w0[7];
            auto load_w0 = [&]() {
                w0[6] = lds128u<3072>(l16, uw); w0[0] = lds128u<0>(l16, uw); w0[1] = lds128u<512>(l16, uw); w0[2] = lds128u<1024>(l16, uw);
                w0[3] = lds128u<1536>(l16, uw); w0[4] = lds128u<2048>(l16, uw); w0[5] = lds128u<2560>(l16, uw);
            };
            load_w0();
            auto put_u = [&](int sl) {
                const uint32_t l4 = add_here(l8, -sb) >> 1;
                uint8_t* p = add_here((uint8_t*)(g_U + (((sl & (RS - 1)) * 64 + bid) * 14 + 4 * w) * 32), l4);
                stg32(p, ub.x); stg32(p + 128, ub.y); stg32(p + (int)u2, ub.z);
                if (!(((l4 >> 4) ^ w) & 1)) stg32(p + (wodd ? -128 : 384), ub.w);
            };
            if (w == 3 && elect_one()) GT(0, 3);
#pragma unroll 1
            for (int s = 0; s < NSEG; s++) {
                const uint32_t ksa = uni(stg + uk);
                mbar_wait(sb + R_BAR + B_KV + s * 8, 0);
                const uint4 k3 = ldsm4u<1536>(lp, ksa);
                uint4 k0 = ldsm4u<0>(lp, ksa);
                const uint4 k1 = ldsm4u<512>(lp, ksa), k2 = ldsm4u<1024>(lp, ksa);
                const uint8_t* pp = add_here(accb + (acc_slot(s) + upoll), lo);
                while ((int)(clk() - t0) < POLL_DELAY) {}
                DBG(0);
                int it = zero;
                uint4 v0 = ld_relaxed4(pp), v1 = ld_relaxed4(pp + 2048), v2 = ld_relaxed4(pp + 16384), v3 = ld_relaxed4(pp + 18432);
                auto take = [&](uint4& v0, uint4& v1, uint4& v2, uint4& v3, uint32_t zr) {
                    const uint32_t mn = umin3(umin3(v0.w, v1.w, ~zr), v2.w, v3.w), sel = 0x5410u ^ (mn & zr);
                    const bool ok = __all_sync(0xffffffffu, mn >= CNT16);
                    v0.z ^= zr; v0.w = prmt(v0.w, v1.w, sel); v1.z ^= zr; v1.w = v3.z ^ (v0.w & zr); v2.z ^= zr; v2.w = prmt(v2.w, v3.w, sel);
                    sts128u<W_MB>(l16, uw, v0.x, v0.y, v0.z, v0.w); sts128u<W_MB + 512>(l16, uw, v1.x, v1.y, v1.z, v1.w);
                    sts128u<W_MB + 1024>(l16, uw, v2.x, v2.y, v2.z, v2.w); sts64u<W_MB + 1536>(l16, uw, v3.x, v3.y);
                    return ok;
                };
                auto handover = [&](uint32_t z) {
                    bar_sync(BR_MB + z, 256);
                };
                bar_arrive(BR_POLL + w, 64);
                if (!(EXP_MIN & 1)) put_u(s - 1);
                if (zero != 7) {
                    bool ok;
#pragma unroll 1
                    do {
                        if (it) {
                            if (it > SPIN) __trap();
                            v0 = ld_relaxed4(pp); v1 = ld_relaxed4(pp + 2048); v2 = ld_relaxed4(pp + 16384); v3 = ld_relaxed4(pp + 18432);
                        }
                        it++;
                        ok = take(v0, v1, v2, v3, zr);
                    } while (!ok);
                    handover(0);
                }
                const uint32_t b[14] = {v0.x, v0.y, v0.z, v0.w, v1.x, v1.y, v1.z, v1.w, v2.x, v2.y, v2.z, v2.w, v3.x, v3.y};
                DBG(1);
                float acc[7][4], sa[4], sc[4], sx[4], sy[4];
                uint32_t tb[14];
                auto T = [&](int m, int k) { if (k == 0) mmaqz(acc[m], w0[m], b[0], b[1]); else mmaq(acc[m], wr[m][k - 1], b[2 * k], b[2 * k + 1]); };
                auto TR = [&](int m) { tb[2 * m] = movm(pack_bf16(acc[m][0], acc[m][1])); tb[2 * m + 1] = movm(pack_bf16(acc[m][2], acc[m][3])); };
                auto after = [&](uint32_t v, float dep) { return v ^ (__float_as_uint(dep) & zr); };
                T(6, 0); T(0, 0); T(1, 0); T(2, 0);
                T(6, 1); T(0, 1); T(1, 1); T(3, 0);
                T(6, 2); T(0, 2); T(1, 2); T(2, 1);
                T(6, 3); T(0, 3); T(1, 3); T(3, 1);
                T(6, 4); T(0, 4); T(1, 4); T(2, 2);
                T(6, 5); T(0, 5); T(1, 5); T(3, 2);
                T(6, 6); T(0, 6); T(1, 6); T(2, 3);
                w0[4].x = after(w0[4].x, acc[6][0]); w0[5].x = after(w0[5].x, acc[6][1]);
                const uint32_t ld = after(l16, acc[6][2]);
                uint4 am0 = lds128u<W_MB>(ld, uc);
                const uint2 am3 = lds64u<W_MB + 1536>(ld, uc);
                k0.x = after(k0.x, acc[1][0]);
                DBG(2);
                T(3, 3); T(4, 0); T(5, 0); T(2, 4);
                TR(6); TR(0); TR(1);
                T(3, 4); T(4, 1); T(5, 1); T(2, 5);
                T(3, 5); T(4, 2); T(5, 2); T(2, 6);
                T(3, 6); T(4, 3); T(5, 3);
                am0.x = after(am0.x, acc[2][0]);
                const uint32_t ld2 = after(l16, acc[2][1]);
                uint4 am1 = lds128u<W_MB + 512>(ld2, uc);
                const uint4 am2 = lds128u<W_MB + 1024>(ld2, uc);
                mmaqz(sx, k0, b[0], b[1]); mmaqz(sy, k0, b[2], b[3]);
                T(4, 4); T(5, 4);
                TR(2); TR(3);
                mmaqz(sa, am0, tb[0], tb[2]); mmaqz(sc, am0, tb[1], tb[3]);
                T(4, 5); T(5, 5);
                mmaq(sx, k1, b[4], b[5]); mmaq(sy, k1, b[6], b[7]);
                T(4, 6); T(5, 6);
                mma1688(sa, am3.x, am3.y, tb[12]); mma1688(sc, am3.x, am3.y, tb[13]);
                mmaq(sx, k2, b[8], b[9]); mmaq(sy, k2, b[10], b[11]);
                am1.x = after(am1.x, acc[4][0]);
                TR(4); TR(5);
                mmaq(sa, am1, tb[4], tb[6]); mmaq(sc, am1, tb[5], tb[7]);
                mmaq(sx, k3, b[12], b[13]);
                sts64u<W_SMI + 256>(l8, uw, __float_as_uint(sx[0] + sy[2]), __float_as_uint(sx[1] + sy[3]));
                bar_arrive(ugo ^ (tb[GO_DEP] & zr), 64);
                mmaq(sa, am2, tb[8], tb[10]); mmaq(sc, am2, tb[9], tb[11]);
                const uint4 tc = lds128u<W_TAB + 512>(l16, uw), ra = lds128u<W_TAB>(l16, uw);
                const uint32_t va3 = tc.x, ua = tc.y, ua3 = tc.z;
                lp = tc.w;
                uint2 vb[4][2];
                const uint32_t va = uni(stg + uv), va2 = uni(va + 4 * u2);
                auto load_v0 = [&]() { vb[0][0] = lds64u<0>(l8, va); vb[1][0] = lds64u<512>(l8, va); vb[2][0] = lds64u<0>(l8, va2); };
                auto load_v1 = [&]() {
                    vb[0][1] = lds64u<256>(l8, va); vb[1][1] = lds64u<768>(l8, va); vb[2][1] = lds64u<256>(l8, va2);
                    vb[3][0] = lds64u<0>(va3, stg); vb[3][1] = lds64u<256>(va3, stg);
                };
                if (VEARLY >= 1) load_v0();
                if (XFENCE) SCHED_FENCE(zero, 4);
                sts64u<W_SMI>(l8, uw, __float_as_uint(sa[0] + sc[2]), __float_as_uint(sa[1] + sc[3]));
                DBG(3);
                bar_sync(BR_SM, 128);
                {
                    const float2 p0 = lds64f(sia), p1 = lds64f(sia + WB), p2 = lds64f(sia + 2 * WB), p3 = lds64f(sia + 3 * WB);
                    if (VEARLY == 0) load_v0();
                    if (VEARLY <= 1) load_v1();
                    asm volatile("{.reg .pred p; .reg .f32 a,b; .reg .b32 e; setp.lt.u32 p,%6,2; @p bra.uni S;\n"
                                 "ex2.approx.ftz.f32 a,%4; ex2.approx.ftz.f32 b,%5; cvt.rn.bf16x2.f32 e,b,a;\n"
                                 "st.async.weak.shared::cluster.mbarrier::complete_tx::bytes.u32 [%0],e,[%1];\n"
                                 "st.async.weak.shared::cluster.mbarrier::complete_tx::bytes.u32 [%2],e,[%3]; bra.uni D;\n"
                                 "S: st.async.weak.shared::cluster.mbarrier::complete_tx::bytes.v2.f32 [%0],{%4,%5},[%1];\n"
                                 "st.async.weak.shared::cluster.mbarrier::complete_tx::bytes.v2.f32 [%2],{%4,%5},[%3];\n"
                                 "D:}" ::"r"(ra.x), "r"(ra.y), "r"(ra.z), "r"(ra.w), "f"((p0.x + p1.x) + (p2.x + p3.x)), "f"((p0.y + p1.y) + (p2.y + p3.y)), "r"(w) : "memory");
                }
                DBG(4);
                if (VEARLY == 2) load_v1();
                if (!(EXP_MIN & 4)) {
                stsm4u<S_TB - S_KO>(lp, ksa, tb[0], tb[2], tb[1], tb[3]); stsm4u<S_TB - S_KO + 512>(lp, ksa, tb[4], tb[6], tb[5], tb[7]);
                stsm4u<S_TB - S_KO + 1024>(lp, ksa, tb[8], tb[10], tb[9], tb[11]); stsm2u<S_TB - S_KO + 1536>(l16, ksa, tb[12], tb[13]);
                }
                uint8_t* rp = add_here(accb + (acc_slot(s + 1) + ured), lo);
                float o[4][4];
                auto pv_x = [&](const uint4& e01, const uint4& e23) {
#pragma unroll
                    for (int q = 3; q < 7; q++) mmaqz(o[q & 3], e01, vb[q & 3][0].x, vb[q & 3][0].y);
#pragma unroll
                    for (int q = 3; q < 7; q++) mmaq(o[q & 3], e23, vb[q & 3][1].x, vb[q & 3][1].y);
                };
                auto pv_m = [&](float f0, float f1) {
                    const uint32_t pm = pack_bf16(f0, f1), j = __float_as_uint(f0);
                    mma1688(o[3], pm, j, ub.w); mma1688(o[0], pm, j, ub.x); mma1688(o[1], pm, j, ub.y); mma1688(o[2], pm, j, ub.z);
                };
                auto finish = [&](bool on) {
                    const float r = rcp(wodd ? o[3][0] : o[3][1]);
                    red_bf16x8(rp, on, pack_bf16(o[0][0] * r, o[0][1] * r), pack_bf16(o[1][0] * r, o[1][1] * r),
                               pack_bf16(o[2][0] * r, o[2][1] * r), pack_bf16((wodd ? o[3][1] : o[3][0]) * r, 1.0f));
                    t0 = clk();
                    DBG(9);
                    load_w0();
                };
                mbar_wait_cl(sb + R_BAR + B_SM, s & 1);
                DBG(5);
                float x0, x1;
                {
                    const uint4 e = ldsm4tu<R_SMM + 1024>(lp, 0);
                    const float2 p0 = lds64fu<R_SMM>(l8, 0), p1 = lds64fu<R_SMM + 256>(l8, 0), p2 = lds64fu<R_SMM + 512>(l8, 0), p3 = lds64fu<R_SMM + 768>(l8, 0);
                    bar_sync(BR_UP, 256);
                    x0 = (p0.x + p1.x) + (p2.x + p3.x); x1 = (p0.y + p1.y) + (p2.y + p3.y);
                    pv_x(e, make_uint4(e.y ^ zr, __float_as_uint(x0), e.w ^ zr, __float_as_uint(x1)));
                }
                DBG(6);
                {
                    const float f0 = ex2(x0), f1 = ex2(x1);
                    const uint32_t a3 = UPIN == 2 ? ua3 : after(ua3, UPIN == 0 ? x0 : f0), a0 = UPIN == 2 ? ua : after(ua, UPIN == 0 ? x0 : f0);
                    const uint4 u3 = ldsm4q(a3), u0 = ldsm4q(a0), u1 = ldsm4q(a0 + 128), uu = ldsm4u<0>(a0, u2);
                    ub = make_uint4(hsum4(u0.x, u0.y, u0.z, u0.w), hsum4(u1.x, u1.y, u1.z, u1.w), hsum4(uu.x, uu.y, uu.z, uu.w), hsum4(u3.x, u3.y, u3.z, u3.w));
                    pv_m(f0, f1);
                }
                const bool safe = __all_sync(0xffffffffu, __float_as_uint(wodd ? o[3][0] : o[3][1]) - SAFE_LO < SAFE_SPAN);
                finish(safe);
                if (!safe) {
                    float y[8];
#pragma unroll
                    for (int q = 0; q < 8; q++) {
                        const uint32_t ln = add_here(l8, -sb) >> 3;
                        const uint32_t a = mapa(sb + R_WB + W_SMI + 256 + (2 * (ln & 3) + (q & 1)) * 32 + (ln >> 2) * 4, (q >> 1));
                        y[q] = (ldr32f(a) + ldr32f(a + WB)) + (ldr32f(a + 2 * WB) + ldr32f(a + 3 * WB));
                    }
                    float m = fmaxf(x0, x1);
#pragma unroll
                    for (int q = 0; q < 8; q++) m = fmaxf(m, y[q]);
                    m = fmaxf(m, __shfl_xor_sync(0xffffffffu, m, 1)); m = fmaxf(m, __shfl_xor_sync(0xffffffffu, m, 2));
                    load_v0(); load_v1();
                    pv_x(make_uint4(pack_bf16(ex2(y[0] - m), ex2(y[1] - m)), 0u, pack_bf16(ex2(y[2] - m), ex2(y[3] - m)), 0u),
                         make_uint4(pack_bf16(ex2(y[4] - m), ex2(y[5] - m)), 0u, pack_bf16(ex2(y[6] - m), ex2(y[7] - m)), 0u));
                    pv_m(ex2(x0 - m), ex2(x1 - m));
                    finish(zero == 0);
                }
                bar_arrive(BR_RED, 256);
                stg = uni(stg == R_STG + 2 * STGB ? R_STG : stg + STGB);
            }
            bar_arrive(BR_POLL + w, 64);
            put_u(NSEG - 1);
            bar_arrive(BR_PRO, 160);
        } else {
            const int lane = fresh_lane(), g = lane >> 2, t = lane & 3;
            const uint32_t l16 = sb + lane * 16, l8 = sb + lane * 8, wsa = l16 + R_WB + wid * WB;
            uint4 wr[7][6];
            load_weights(wr, lane);
            auto gather_rows = [&](int sl, float (&v)[10]) {
                const uint32_t a = R_LS + (sl & 1) * 5120;
                const float4 q0 = sum4(lds128f(l16 + a), lds128f(l16 + a + 1280), lds128f(l16 + a + 2560), lds128f(l16 + a + 3840));
                const float4 q1 = sum4(lds128f(l16 + a + 512), lds128f(l16 + a + 1792), lds128f(l16 + a + 3072), lds128f(l16 + a + 4352));
                const float2 p0 = lds64f(l8 + a + 1024), p1 = lds64f(l8 + a + 2304), p2 = lds64f(l8 + a + 3584), p3 = lds64f(l8 + a + 4864);
                const float z[8] = {q0.x, q0.y, q0.z, q0.w, q1.x, q1.y, q1.z, q1.w};
                v[8] = (p0.x + p1.x) + (p2.x + p3.x); v[9] = (p0.y + p1.y) + (p2.y + p3.y);
                const int lim = 8 * c + g - 2 * t;
#pragma unroll
                for (int i = 0; i < 8; i++) v[i] = (8 * (i >> 1) + (i & 1) <= lim) ? z[i] : -INFINITY;
            };
            auto softmax_rows = [&](int sl, const float (&v)[10], bool gate) {
                float e[10], l[4];
                auto expo = [&](float m) {
#pragma unroll
                    for (int i = 0; i < 10; i++) e[i] = ex2(v[i] - m);
                    mma16816z(l, pack_bf16(e[0], e[1]), pack_bf16(e[4], e[5]), pack_bf16(e[2], e[3]), pack_bf16(e[6], e[7]), ONE2, ONE2);
                    mma1688(l, pack_bf16(e[8], e[9]), 0u, ONE2);
                    l[0] += l[2];
                };
                expo(0.f);
                if (__builtin_expect(__any_sync(0xffffffffu, __float_as_uint(l[0]) - SAFE_LO >= SAFE_SPAN), 0)) {
                    float m = v[0];
#pragma unroll
                    for (int i = 1; i < 10; i++) m = fmaxf(m, v[i]);
                    m = fmaxf(m, __shfl_xor_sync(0xffffffffu, m, 1)); m = fmaxf(m, __shfl_xor_sync(0xffffffffu, m, 2));
                    expo(m);
                }
                const float r = rcp(l[0]);
                uint8_t* pd = add_here((uint8_t*)(g_P + (((sl & (RS - 1)) * 16 + h) * 14 + (c * (c + 3) >> 1)) * 32), lane * 4);
                if (gate) bar_sync((BR_POLL + 2) ^ (__float_as_uint(r) & zero), 64);
#pragma unroll
                for (int q = 0; q < 4; q++) if (q <= c) stg32(pd + q * 128, pack_bf16(e[2 * q] * r, e[2 * q + 1] * r));
                stg32(pd + (c + 1) * 128, pack_bf16(e[8] * r, e[9] * r));
                __syncwarp();
                mbar_arrive_if(lane == 0, sb + R_BAR + B_PUB + sl * 8);
            };
            uint4 wx[URES + 1];
#pragma unroll
            for (int m = 0; m < URES; m++) wx[m] = lds128(wsa + m * 512);
            bar_sync(BR_POLL + w, 64);
#pragma unroll 1
            for (int s = 0; s < NSEG; s++) {
                const uint32_t stg = R_STG + (s % 3) * STGB;
                uint4 w0[7];
#pragma unroll
                for (int m = 0; m < 7 - UW0; m++) w0[m] = m < URES ? wx[m] : lds128(wsa + m * 512);
                bar_sync(BR_MB, 256);
                mbar_arrive_if(lane + w == 0, sb + R_BAR + B_H + s * 8);
                const uint32_t ba = wsa - 4 * WB + W_MB;
                const uint4 b0 = lds128(ba), b1 = lds128(ba + 512), b2 = lds128(ba + 1024);
                const uint2 b3 = lds64(ba + 1536);
#pragma unroll
                for (int m = 7 - UW0; m < 7; m++) w0[m] = lds128(wsa + m * 512);
                bar_sync(BR_GO + w, 64);
                SCHED_FENCE(zero, 2);
                DBG(11);
                float acc[7][4];
                const uint32_t b[14] = {b0.x, b0.y, b0.z, b0.w, b1.x, b1.y, b1.z, b1.w, b2.x, b2.y, b2.z, b2.w, b3.x, b3.y};
                auto U = [&](int m, int k) { if (k == 0) mmaqz(acc[m], w0[m], b[0], b[1]); else mmaq(acc[m], wr[m][k - 1], b[2 * k], b[2 * k + 1]); };
#pragma unroll
                for (int k = 0; k < 7; k++) { U(0, k); U(1, k); U(6, k); U(2 + (k & 3), k >> 2); }
                wr[5][0].x ^= __float_as_uint(acc[0][0]) & zero; wr[2][1].x ^= __float_as_uint(acc[1][0]) & zero;
                wr[3][1].x ^= __float_as_uint(acc[6][0]) & zero; wr[4][1].x ^= __float_as_uint(acc[6][1]) & zero;
                U(5, 1);
#pragma unroll
                for (int k = 2; k < 7; k++) { U(2, k); U(3, k); U(4, k); U(5, k); }
                {
                    const uint32_t a = wsa + W_UP;
                    stsm2(a + 1536, pack_bf16(acc[6][0], acc[6][1]), pack_bf16(acc[6][2], acc[6][3]));
#pragma unroll
                    for (int q = 0; q < 3; q++)
                        stsm4(a + q * 512, make_uint4(pack_bf16(acc[2 * q][0], acc[2 * q][1]), pack_bf16(acc[2 * q][2], acc[2 * q][3]),
                                                      pack_bf16(acc[2 * q + 1][0], acc[2 * q + 1][1]), pack_bf16(acc[2 * q + 1][2], acc[2 * q + 1][3])));
                }
                bar_arrive(BR_UP, 256);
                DBG(12);
                if (w == 2 && s > 0 && !(EXP_MIN & 2)) mbar_wait_cl(sb + R_BAR + B_LS + (s - 1) * 8, 0);
                bar_sync(BR_RED, 256);
                if (EXP_MIN & 2) { if (w == 3 && elect_one()) mbar_expect(sb + R_BAR + B_SM, 1536); bar_sync(BR_POLL + w, 64); mbar_arrive_if(lane == 0 && w == 2, sb + R_BAR + B_PUB + s * 8); } else
                {
                    float y[32], v[10];
#pragma unroll
                    for (int i = 0; i < 10; i++) v[i] = 0.f;
                    if (GFIRST && w == 2 && s > 0) gather_rows(s - 1, v);
                    const uint64_t da = sdesc(sb + stg + S_X, 16, 1024, 1), db = sdesc(sb + stg + S_KS, 128, 1792, 0);
                    asm volatile("fence.proxy.async.shared::cta;" ::: "memory");
                    wg_fence();
#pragma unroll
                    for (int k = 0; k < 7; k++) wgmma64(y, da + (k >> 2) * 256 + (k & 3) * 2, db + k * 16, k);
                    wg_commit();
                    wg_wait<0>();
                    if (w < 2) {
                        const uint32_t r0 = mapa(sb, 2 * w), r1 = mapa(sb, 2 * w + 1);
                        const uint32_t o = R_LS + (s & 1) * 5120 + c * 1280 + lane * 16, lb = R_BAR + B_LS + s * 8;
                        bar_sync(BR_POLL + w, 64);
                        st_async4(r0 + o, r0 + lb, y[0], y[1], y[4], y[5]); st_async4(r1 + o, r1 + lb, y[2], y[3], y[6], y[7]);
                        if (w == 1) { st_async4(r0 + o + 512, r0 + lb, y[8], y[9], y[12], y[13]); st_async4(r1 + o + 512, r1 + lb, y[10], y[11], y[14], y[15]); }
                        st_async2(r0 + o + 1024 - lane * 8, r0 + lb, (y[16] + y[20]) + (y[24] + y[28]), (y[17] + y[21]) + (y[25] + y[29]));
                        st_async2(r1 + o + 1024 - lane * 8, r1 + lb, (y[18] + y[22]) + (y[26] + y[30]), (y[19] + y[23]) + (y[27] + y[31]));
                    } else if (w == 2 && s > 0) { if (!GFIRST) gather_rows(s - 1, v); softmax_rows(s - 1, v, true); }
                    else {
                        if (w == 3 && elect_one()) mbar_expect(sb + R_BAR + B_SM, 1536);
                        if (s >= 3) mbar_wait(sb + R_BAR + B_Z + (s - 3) * 8, 0);
                        bar_sync(BR_POLL + w, 64);
                    }
                }
                DBG(13);
                DBG(14);
            }
            if (EXP_MIN & 2) { if (w == 2) bar_sync(BR_PRO, 160); } else
            if (w == 2) { bar_sync(BR_PRO, 160); mbar_wait_cl(sb + R_BAR + B_LS + (NSEG - 1) * 8, 0); float v[10]; gather_rows(NSEG - 1, v); softmax_rows(NSEG - 1, v, false); }
        }
        cluster_arrive_rel(); cluster_wait();
    } else {
        asm volatile("setmaxnreg.dec.sync.aligned.u32 24;");
        const unsigned epoch = uni(ld_relaxed(&g_EXIT) / ntotal);
        const int lane = fresh_lane();
        if (elect_one()) {
#pragma unroll 1
            for (int i = w; i < 384; i += 4) {
                mbar_init(sb + R_BAR + i * 8, 1);
                if (i < 192) mbar_expect(sb + R_BAR + i * 8, i < 64 ? S_TB : (i < 128 ? 1536 : (c < 2 ? 3072 : 5120)));
            }
            asm volatile("fence.mbarrier_init.release.cluster;" ::: "memory");
            asm volatile("fence.proxy.async.shared::cta;" ::: "memory");
        }
        __syncwarp();
        bar_sync(BR_H, 128);
        cluster_arrive();
        if (w == 0) {
            sts32(sb + R_MISC, epoch);
            wait_count_warp(&g_INIT, (epoch + 1) * 64, 100);
            fence_acq();
            bar_sync(BR_ALL, 288);
            const unsigned* ft = g_FT + (lane < 2 ? 2 * h + lane : 32 + 2 * h + (c >> 1)) * 32;
#pragma unroll 1
            for (int seg = 0; seg < NSEG; seg++) {
                if (!(seg & 1)) {
                    wait_count_warp(ft + (~(seg >> 1) & 1), epoch * 32 + (((seg >> 1) + 9) >> 1), seg ? 0 : 40);
                    fence_acq();
                    asm volatile("fence.proxy.async.global;" ::: "memory");
                }
                const uint32_t bar = sb + R_BAR + B_KV + seg * 8, dst = sb + R_STG + (seg % 3) * STGB;
                const uint8_t* kp = g_K + ((seg & (RS - 1)) * 16 + h) * 28672;
                const uint8_t* vp = g_V + (((seg & (RS - 1)) * 16 + h) * 4 + c) * 7168;
                if (seg == 0 && elect_one()) GT(0, 7);
                if (seg >= 2) mbar_wait(sb + R_BAR + B_H + (seg - 2) * 8, 0);
                if (elect_one()) {
                    bulk_g2s(dst + S_KO, kp + c * 7168, 7168, bar);
                    bulk_g2s(dst + S_V, vp, 7168, bar);
                    tma2d(dst + S_X, &mapXs, 112 * c, 32 * seg, bar); tma2d(dst + S_X + 4096, &mapXs, 112 * c + 64, 32 * seg, bar);
#pragma unroll
                    for (int j = 0; j < 4; j++) bulk_g2s(dst + S_KS + j * 1792, kp + j * 7168 + c * 1792, 1792, bar);
                }
                if (seg == 2 && elect_one()) GT(0, 4);
                if (seg == NSEG - 1 && elect_one()) GT(0, 5);
            }
        } else if (w == 1) {
            {
                const int q = h >> 2, l = (h & 3) * 8 + (lane & 7);
                const uint32_t* mp = (const uint32_t*)(mem0 + (l >> 2) * D + 112 * c) + (l & 3);
                uint4 v = make_uint4(0, 0, 0, 0);
                if (lane < 8) v = make_uint4(mp[4 * tile_of(q, 0)], mp[4 * tile_of(q, 1)], mp[4 * tile_of(q, 2)],
                                             ((mp[4 * tile_of(q, 3)] >> (16 * (q & 1))) & 0xffffu) | CNT16);
                *(uint4*)(accb + (acc_off(c, q, l)) + acc_slot(lane >> 3)) = v;
                *(uint4*)(accb + (acc_off(c, q, l)) + acc_slot(4 + (lane >> 3))) = make_uint4(0, 0, 0, 0);
                __syncwarp();
                if (lane == 0) { fence_rel(); red_inc(&g_INIT); }
            }
            __syncwarp();
            uint8_t* zp = accb + (acc_off(c, h >> 2, (h & 3) * 8 + (lane & 7)));
#pragma unroll 1
            for (int seg = 0; seg < NSEG; seg++) {
                mbar_wait(sb + R_BAR + B_PUB + seg * 8, 0);
                if (lane < 8 && seg < NSEG - 8 + ((EXP_MIN >> 1) & 1) && seg >= ((EXP_MIN >> 1) & 1)) *(uint4*)(zp + acc_slot(seg - ((EXP_MIN >> 1) & 1))) = make_uint4(0, 0, 0, 0);
                __syncwarp();
                if (lane == 0) {
                    fence_rel();
                    red_inc(g_CNT + seg * 32); mbar_arrive(sb + R_BAR + B_Z + seg * 8); }
                __syncwarp();
            }
            if (elect_one()) GT(0, 6);
        } else {
            if (w == 2 && PF2) {
                const uint32_t t1 = clk();
                while ((int)(clk() - t1) < PF2) __nanosleep(100);
                if (elect_one()) {
#pragma unroll 1
                    for (int i = 1; i < 7; i++) { prefetch_l2(wk + (i * 64 + bid) * 8192, 8192); prefetch_l2(wv + (i * 64 + bid) * 8192, 8192); }
                    prefetch_l2(x + bid * 28672, 28672);
                }
            }
            if (w == 3 && bid < D / 8) {
#pragma unroll 1
                for (int i = 0; i < 16; i++) {
                    mbar_wait(sb + R_BAR + B_H + i * 8, 0);
                    if (elect_one()) { ssm_store(sb, bid * 8, i, &mapY); asm volatile("cp.async.bulk.wait_group 0;" ::: "memory"); }
                    __syncwarp();
                }
            }
        }
        cluster_wait(); cluster_arrive(); cluster_wait();
        if (w == 1 && lane == 0) red_inc(&g_EXIT);
    }
}
#undef GTB
#define GTB blockIdx.x

constexpr int BLK = 28672;
#define NRING 6
constexpr int G_RING = 7 * BLK;
constexpr int G_SCR = G_RING + NRING * 4096;
constexpr int G_BAR = G_SCR + 6144;
constexpr int G_PUB = G_BAR + 18 * 8;
constexpr int G_RDY = G_PUB + 39 * 8;
constexpr int G_MISC = G_RDY + 8 * 8;
constexpr int G_SMEM = G_MISC + 16;
static_assert(G_SMEM <= 232448, "smem");
#define FPACE 70
#define PACE 120
constexpr int LAG = 4, TAIL = NSEG - 8;
static_assert(LAG + 3 <= RS / 2, "ring");
constexpr int PVS = 37632, PV_U = 28672, PV_P = 35840, PV_N = 6, PV_Z = PV_N * PVS;
static_assert(PV_Z + 16 <= G_BAR, "smem");

struct PvOps { uint2 v[2][14]; uint32_t p[2][14], m[2][7]; };
__device__ __forceinline__ void pv_load_v(PvOps& o, int sh, int G, int lane) {
    const uint8_t* vp = g_V + (sh * 56 + 7 * G) * 512 + lane * 8;
#pragma unroll
    for (int i = 0; i < 28; i++) o.v[i / 14][i % 14] = __ldcg((const uint2*)(vp + (i / 14) * (56 * 512) + (i % 14) * 256));
}
__device__ __forceinline__ void pv_load_pu(PvOps& o, int sh, int G, int lane) {
    const uint32_t* up = g_U + (sh * 56 + 7 * G) * 32 + lane;
    const uint32_t* pp = g_P + sh * 448 + lane;
#pragma unroll
    for (int i = 0; i < 28; i++) o.p[i / 14][i % 14] = __ldcg(pp + i * 32);
#pragma unroll
    for (int i = 0; i < 14; i++) o.m[i / 7][i % 7] = __ldcg(up + (i / 7) * (56 * 32) + (i % 7) * 32);
}
__device__ __forceinline__ void pv_mma(float (&acc)[2][7][4], const PvOps& o) {
#pragma unroll
    for (int j = 0; j < 2; j++) {
        const uint32_t* q = o.p[j];
#pragma unroll
        for (int i = 0; i < 7; i++) mma16816(acc[1][i], q[5], q[9], q[6], q[10], o.v[j][2 * i].x, o.v[j][2 * i].y);
#pragma unroll
        for (int i = 0; i < 7; i++) mma16816(acc[0][i], q[0], q[2], 0u, q[3], o.v[j][2 * i].x, o.v[j][2 * i].y);
#pragma unroll
        for (int i = 0; i < 7; i++) mma16816(acc[1][i], q[7], q[11], 0u, q[12], o.v[j][2 * i + 1].x, o.v[j][2 * i + 1].y);
    }
#pragma unroll
    for (int i = 0; i < 7; i++) {
        mma16816(acc[0][i], o.p[0][1], o.p[0][4], o.p[1][1], o.p[1][4], o.m[0][i], o.m[1][i]);
        mma16816(acc[1][i], o.p[0][8], o.p[0][13], o.p[1][8], o.p[1][13], o.m[0][i], o.m[1][i]);
    }
}
__device__ __forceinline__ int unit_segment(int n, int k, bool spare) { return spare ? (n < 32 ? 16 * k + 4 * (n >> 3) + 3 : NSEG) : 8 * k + (n >> 3); }

__device__ __forceinline__ void pace(uint32_t& t0, int gap) { uint32_t t1; do { t1 = clk(); } while ((int)(t1 - t0) < 0); t0 = t1 + gap; }

template <int NSTG>
__device__ __forceinline__ void tile_mainloop(float* d, uint32_t sb, int slot, uint32_t par, uint64_t db, uint32_t kstep, bool trans,
                                              int lane, int pass_to, bool wait_b) {
    const uint64_t da0 = sdesc(sb + G_RING, 16, 512, 2);
    const uint32_t eb = mapa(sb + G_BAR + 7 * 8, lane & 1);
    int prev = 0;
#pragma unroll
    for (int i = 0; i < NSTG; i++) {
        if (!(i & 1) && wait_b) mbar_wait(sb + G_BAR + (14 + (i >> 1)) * 8, 0);
        mbar_wait(sb + G_BAR + slot * 8, par);
        wg_fence();
        const uint64_t da = da0 + slot * 256, b0 = db + (i >> 1) * (BLK >> 4) + (i & 1) * 2 * kstep;
        if (trans) { wgmma224<1>(d, da, b0, i); wgmma224<1>(d, da + 2, b0 + kstep, 1); }
        else { wgmma224<0>(d, da, b0, i); wgmma224<0>(d, da + 2, b0 + kstep, 1); }
        wg_commit();
        if (i == NSTG - 1 && pass_to) bar_arrive(pass_to, 256);
        if (i > 0) { wg_wait<1>(); mbar_arrive_cl_if(lane < 2, eb + prev * 8); }
        prev = slot;
        if (++slot == NRING) { slot = 0; par ^= 1; }
    }
    wg_wait<0>();
    mbar_arrive_cl_if(lane < 2, eb + prev * 8);
}

template <int M>
__device__ __forceinline__ void fold_role(uint32_t sb, int n, int wg, int u, int lane) {
    const bool lead = lane == 0;
    const uint64_t db = M == 0 ? sdesc(sb + 3 * BLK, 16, 1024, 1) : sdesc(sb + 3 * BLK, 4096, 512, 2);
    const uint32_t sa = sb + (8 * ((lane >> 3) & 1) + (lane & 7)) * 128 + (((2 * u + (lane >> 4)) ^ (lane & 7)) << 4);
    uint4* dst = g_F + (n * 56 + 4 * wg + u) * 224 + lane;
    uint4 q[14], qa[14];
#pragma unroll
    for (int i = 0; i < 14; i++) q[i] = make_uint4(0, 0, 0, 0);
    int blk = wg;
#pragma unroll 1
    for (;; blk += 2, dst += 8 * 224) {
        float d[112];
        bar_sync(1 + wg, 256);
        tile_mainloop<8>(d, sb, (8 * blk) % NRING, ((8 * blk) / NRING) & 1, db, M == 0 ? 2 : 64, M == 1, lane, 2 - wg, blk < 2);
        if (u == 0 && lead) GT(1, 6 + blk);
        const float sc = M ? 1.f : 0.0625f * LOG2E;
#pragma unroll
        for (int i = 0; i < 14; i++) {
            const float* e = d + 8 * i;
            qa[i] = q[i];
            q[i] = make_uint4(pack_bf16(e[0] * sc, e[1] * sc), pack_bf16(e[4] * sc, e[5] * sc), pack_bf16(e[2] * sc, e[3] * sc), pack_bf16(e[6] * sc, e[7] * sc));
        }
        auto handover = [&]() {
            bar_sync(3, 256);
#pragma unroll
            for (int i = 0; i < 14; i++) { stsm4t(sa + (blk - 2) * BLK + i * 2048, qa[i]); stsm4t(sa + blk * BLK + i * 2048, q[i]); }
            asm volatile("fence.proxy.async.shared::cta;" ::: "memory");
            bar_sync(3, 256);
        };
        if (blk == 6) { handover(); if (u == 0 && lead) GT(1, 13); }
        uint32_t t0 = clk();
#pragma unroll
        for (int i = 0; i < 14; i++) {
            pace(t0, FPACE);
            dst[(i / 7) * (28 * 224) + (i % 7) * 32] = q[i];
            if (blk < 3) stsm4t(sa + blk * BLK + i * 2048, q[i]);
        }
        __syncwarp();
        mbar_arrive_if(lead, sb + G_PUB + blk * 8);
        if (blk == 5) handover();
        if (blk >= 5) break;
    }
}

__device__ __forceinline__ void bulk_consumer(uint32_t sb, int n, unsigned epoch, __nv_bfloat16* __restrict__ out, int phases, bool spare) {
    const int lane = fresh_lane(), wid = __shfl_sync(0xffffffffu, threadIdx.x >> 5, 0), wg = wid >> 2, u = wid & 3;
    const int h = (n >> 1) & 15, hf = n & 1;
    const bool lead = lane == 0;
    if (phases & 1) {
        if (wg == 1) bar_arrive(1, 256);
        if (n < 32) fold_role<0>(sb, n, wg, u, lane); else fold_role<1>(sb, n, wg, u, lane);
        bar_sync(1 + wg, 256);
    }
    const uint64_t db = sdesc(sb, 16, 1024, 1);
    float acc[2][7][4];
#pragma unroll
    for (int i = 0; i < 56; i++) (&acc[0][0][0])[i] = 0.f;
#pragma unroll 1
    for (int tile = 1 - wg; tile < LAG + TAIL / 2 + 5; tile += 2) {
        const bool gemm = tile < 32 && (phases & 1);
        uint32_t y[56];
        if (gemm) {
            float d[112];
            tile_mainloop<14>(d, sb, (56 + 14 * tile) % NRING, ((56 + 14 * tile) / NRING) & 1, db, 2, false, lane, tile == 31 ? 0 : 2 - wg, false);
#pragma unroll
            for (int i = 0; i < 56; i++) y[i] = pack_bf16(d[2 * i], d[2 * i + 1]);
        } else {
#pragma unroll
            for (int i = 0; i < 56; i++) y[i] = 0;
        }
        const int lp = spare ? 3 : 2, rel = tile - LAG - (unit_segment(n, 0, spare) >> 1), ph = rel & ((1 << lp) - 1);
        const int useg = unit_segment(n, rel >> lp, spare), pseg = unit_segment(n, (rel - 4) >> lp, spare);
        const bool batch = rel >= 0 && (ph == 0 || ph == 2) && useg < TAIL && (phases & 2);
        PvOps ops;
        if (batch) {
            if (ph == 0) mbar_wait(sb + G_RDY + (rel >> lp) * 8, 0);
            const int sh = (useg & (RS - 1)) * 16 + 4 * u + ph;
            pv_load_v(ops, sh, n & 7, lane); pv_load_pu(ops, sh, n & 7, lane);
        } else {
#pragma unroll
            for (int j = 0; j < 2; j++) {
#pragma unroll
                for (int i = 0; i < 14; i++) { ops.v[j][i] = make_uint2(0u, 0u); ops.p[j][i] = 0u; if (i < 7) ops.m[j][i] = 0u; }
            }
        }
        if (gemm) {
            const int slot = (2 * tile + (u >> 1)) & (RS - 1);
            if (tile >= RS / 2)
                wait_count_warp(n < 32 ? g_CNT + (2 * tile + 1 - RS) * 32 : g_WD + (tile - RS / 2) * 32, (epoch + 1) * 64, 100);
            uint32_t t0 = clk();
            const int gap = tile > 1 && !batch ? PACE : FPACE;
            if (n < 32) {
                uint8_t* rec = g_K + (((slot * 16 + h) * 4 + 2 * (u & 1)) * 56 + 28 * hf) * 128 + lane * 4;
#pragma unroll
                for (int i = 0; i < 28; i++) {
                    if (!(i & 1)) pace(t0, gap);
                    stg32(rec + i * 128, y[2 * i]); stg32(rec + 7168 + i * 128, y[2 * i + 1]);
                }
            } else {
                uint8_t* rec = g_V + ((slot * 16 + h) * 56 + 28 * hf) * 512 + (u & 1) * 256 + lane * 8;
#pragma unroll
                for (int i = 0; i < 28; i++) {
                    if (!(i & 1)) pace(t0, gap);
                    *(uint2*)(rec + i * 512) = make_uint2(movm(y[2 * i]), movm(y[2 * i + 1]));
                }
            }
            __syncwarp();
            mbar_arrive_if(lead, sb + G_PUB + (7 + tile) * 8);
        }
        if (rel >= 4 && ph == (4 & ((1 << lp) - 1)) && pseg < TAIL && (phases & 2)) {
            uint32_t* o = (uint32_t*)(out + (size_t)(pseg * 32 + 8 * u + (lane >> 2)) * OUTW + D + 56 * (n & 7)) + (lane & 3);
            const uint32_t sc = sb + G_SCR + lane * 16;
#pragma unroll
            for (int i = 0; i < 7; i += 2) {
                const int i1 = i < 6 ? i + 1 : i;
                float4 own = make_float4(0.f, 0.f, 0.f, 0.f);
#pragma unroll
                for (int r = 0; r < 4; r++) {
                    const float* a = acc[r >> 1][i] + 2 * (r & 1); const float* b = acc[r >> 1][i1] + 2 * (r & 1);
                    if (r == u) own = make_float4(a[0], a[1], b[0], b[1]);
                    else sts128(sc + (r * 3 + ((u - r - 1) & 3)) * 512, __float_as_uint(a[0]), __float_as_uint(a[1]), __float_as_uint(b[0]), __float_as_uint(b[1]));
                }
                bar_sync(4, 128);
                const float4 z = sum4(own, lds128f(sc + u * 1536), lds128f(sc + u * 1536 + 512), lds128f(sc + u * 1536 + 1024));
                bar_sync(4, 128);
                o[4 * i] = pack_bf16(z.x, z.y);
                if (i < 6) o[4 * i + 4] = pack_bf16(z.z, z.w);
            }
#pragma unroll
            for (int i = 0; i < 56; i++) (&acc[0][0][0])[i] = 0.f;
        }
        if (tile < 30 && (phases & 1)) bar_sync(1 + wg, 256);
        if (batch) {
            pv_mma(acc, ops);
            uint32_t dep = __float_as_uint(acc[0][0][0]);
#pragma unroll
            for (int k = 0; k < 7; k++) dep |= __float_as_uint(acc[1][k][0]);
            if (ph == 2 && lead) red_add(g_WD + (useg >> 1) * 32 + (dep & (phases >> 8)), 1);
        }
    }
    cluster_arrive_rel();
    if (!(phases & 2)) return;
    const int seg = TAIL + (n >> 3), sh = (seg & (RS - 1)) * 16 + 2 * wid, q = 7 + (seg >> 1);
    wait_count_warp(g_FT + (32 + 4 * wid + 2 * (lane & 1) + ((n >> 2) & 1)) * 32 + (q & 1), epoch * 32 + (q >> 1) + 1, 50);
    fence_acq();
    PvOps ops;
    pv_load_v(ops, sh, n & 7, lane);
    bar_sync(3, 256);
    mbar_wait(sb + G_RDY + 7 * 8, 0);
    pv_load_pu(ops, sh, n & 7, lane);
    pv_mma(acc, ops);
    const uint32_t wa = sb + wid * 7168 + (lane >> 2) * 224 + (lane & 3) * 8;
#pragma unroll
    for (int i = 0; i < 14; i++) { const float* a = acc[i / 7][i % 7]; sts64f(wa + (i / 7) * 3584 + (i % 7) * 32, a[0], a[1]); sts64f(wa + (i / 7) * 3584 + 1792 + (i % 7) * 32, a[2], a[3]); }
    bar_sync(3, 256);
    if (wid < 7) {
        const int i = wid * 32 + lane, r = i / 7;
        const uint32_t a = sb + i * 32;
        float4 x[2];
#pragma unroll
        for (int j = 0; j < 2; j++) {
            const float4 lo = sum4(lds128f(a + 16 * j), lds128f(a + 16 * j + 7168), lds128f(a + 16 * j + 2 * 7168), lds128f(a + 16 * j + 3 * 7168));
            const float4 hi = sum4(lds128f(a + 16 * j + 4 * 7168), lds128f(a + 16 * j + 5 * 7168), lds128f(a + 16 * j + 6 * 7168), lds128f(a + 16 * j + 7 * 7168));
            x[j] = make_float4(lo.x + hi.x, lo.y + hi.y, lo.z + hi.z, lo.w + hi.w);
        }
        *(uint4*)(out + (size_t)(seg * 32 + r) * OUTW + D + 56 * (n & 7) + 8 * (i - 7 * r)) =
            make_uint4(pack_bf16(x[0].x, x[0].y), pack_bf16(x[0].z, x[0].w), pack_bf16(x[1].x, x[1].y), pack_bf16(x[1].z, x[1].w));
    }
}

__device__ __forceinline__ int spare_segment(int i) { return i + i / 3; }
__device__ __forceinline__ void spare_consumer(uint32_t sb, int j, __nv_bfloat16* __restrict__ out, uint32_t zero) {
    const int lane = fresh_lane(), wid = __shfl_sync(0xffffffffu, threadIdx.x >> 5, 0), mi = lane >> 3;
    if (wid == 0) sts128(sb + PV_Z, 0u, 0u, 0u, 0u);
    bar_sync(3, 256);
    const uint32_t row = sb + (lane & 7) * 16, va = sb + wid * 3584 + lane * 8, ua = sb + PV_U + wid * 896 + lane * 16;
    const uint32_t pa[4] = {row + PV_P + ((0x3020 >> (4 * mi)) & 15) * 128, row + PV_P + ((0xa695 >> (4 * mi)) & 15) * 128,
                            row + PV_P + ((0xc0b7 >> (4 * mi)) & 15) * 128, row + PV_P + ((0xd841 >> (4 * mi)) & 15) * 128};
    int slot = 0; uint32_t par = 0;
#pragma unroll 1
    for (int i = j; spare_segment(i) < TAIL; i += 4) {
        const int seg = spare_segment(i);
        float acc[2][7][4];
#pragma unroll
        for (int k = 0; k < 56; k++) (&acc[0][0][0])[k] = 0.f;
#pragma unroll 1
        for (int h = 0; h < 16; h++) {
            const uint32_t so = slot * PVS;
            mbar_wait(sb + G_BAR + slot * 8, par);
            const uint4 q0 = ldsm4q(mi == 2 ? sb + PV_Z : pa[0] + so), q1 = ldsm4q(pa[1] + so), q2 = ldsm4q(mi == 2 ? sb + PV_Z : pa[2] + so), q3 = ldsm4q(pa[3] + so);
            const uint4 m0 = ldsm4q(ua + so), m1 = ldsm4q(ua + so + 384);
            const uint32_t m[7] = {m0.x, m0.y, m0.z, m1.x, m1.y, m1.z, m1.w};
            uint2 v[14];
#pragma unroll
            for (int k = 0; k < 14; k++) v[k] = lds64(va + so + k * 256);
#pragma unroll
            for (int k = 0; k < 7; k++) { mmaq(acc[1][k], q1, v[2 * k].x, v[2 * k].y); mmaq(acc[0][k], q0, v[2 * k].x, v[2 * k].y); }
#pragma unroll
            for (int k = 0; k < 7; k++) { mmaq(acc[1][k], q2, v[2 * k + 1].x, v[2 * k + 1].y); mma1688(acc[0][k], q3.x, q3.y, m[k]); }
#pragma unroll
            for (int k = 0; k < 7; k++) mma1688(acc[1][k], q3.z, q3.w, m[k]);
            __syncwarp();
            uint32_t dep = 0;
#pragma unroll
            for (int k = 0; k < 7; k++) dep |= __float_as_uint(acc[1][k][0]);
            mbar_arrive_if(lane == 0, sb + G_BAR + (7 + slot) * 8 + ((dep | __float_as_uint(acc[0][0][0])) & zero));
            if (++slot == PV_N) { slot = 0; par ^= 1; }
        }
        if (lane == 0) red_add(g_WD + (seg >> 1) * 32, 4);
        uint32_t* o = (uint32_t*)(out + (size_t)(seg * 32 + (lane >> 2)) * OUTW + D + 56 * wid) + (lane & 3);
#pragma unroll
        for (int k = 0; k < 28; k++) o[(k / 7) * (8 * OUTW / 2) + 4 * (k % 7)] = pack_bf16(acc[k / 14][k % 7][2 * ((k / 7) & 1)], acc[k / 14][k % 7][2 * ((k / 7) & 1) + 1]);
    }
}

__global__ void __cluster_dims__(2, 1, 1) __launch_bounds__(384, 1)
k_bulk(const __grid_constant__ CUtensorMap mapX, const __grid_constant__ CUtensorMap mapK, const __grid_constant__ CUtensorMap mapV,
       const __grid_constant__ CUtensorMap mapQ, const __grid_constant__ CUtensorMap mapO, __nv_bfloat16* __restrict__ out, unsigned ntotal, int phases) {
    extern __shared__ __align__(1024) uint8_t smem[];
    const uint32_t sb = smem_u32(smem);
    const int n = blockIdx.x, wid = __shfl_sync(0xffffffffu, threadIdx.x >> 5, 0);
    const bool spare = gridDim.x >= 68;
    if (threadIdx.x == 0) GT(1, 0);
    if (elect_one()) {
        if (wid >= 8) {
            const int i = wid - 8, h = (n >> 1) & 15, hf = n & 1;
            const uint32_t bar = sb + G_BAR + (14 + i) * 8;
            mbar_init(bar, 1);
            asm volatile("fence.proxy.async.shared::cta;" ::: "memory");
            if (n < 64 && (phases & 1)) {
                mbar_expect(bar, BLK);
                if (n < 32) tma2d(sb + (3 + i) * BLK, &mapQ, h * DH + 64 * i, 224 * hf, bar);
                else tma3d(sb + (3 + i) * BLK, &mapO, 0, h * DH + 64 * i, 7 * hf, bar);
            }
        } else {
            if (wid < 7) { mbar_init(sb + G_BAR + wid * 8, 1); mbar_init(sb + G_BAR + (7 + wid) * 8, 8); }
            asm volatile("fence.mbarrier_init.release.cluster;" ::: "memory");
            asm volatile("fence.proxy.async.shared::cta;" ::: "memory");
        }
    }
    __syncwarp();
    cluster_arrive(); cluster_wait();
    if (wid < 8) {
        asm volatile("setmaxnreg.inc.sync.aligned.u32 240;");
        if (elect_one()) {
#pragma unroll 1
            for (int i = wid; i < 47; i += 8) mbar_init(sb + G_PUB + i * 8, i < 39 ? 4 : 1);
        }
        const unsigned epoch = uni(ld_relaxed(&g_EXIT) / ntotal);
        bar_sync(5, 352);
        if (n < 64) bulk_consumer(sb, n, epoch, out, phases, spare);
        else { cluster_arrive(); if (spare && n < 68 && (phases & 2)) spare_consumer(sb, n - 64, out, phases >> 8); }
        if (wid == 0 && elect_one()) GT(1, 5);
        cluster_wait();
    } else {
        asm volatile("setmaxnreg.dec.sync.aligned.u32 24;");
        cluster_arrive();
        unsigned epoch = 0;
        if (wid > 8) { epoch = uni(ld_relaxed(&g_EXIT) / ntotal); bar_sync(5, 352); }
        if (wid == 9 && elect_one()) red_inc(&g_EXIT);
        if (n < 64) {
            if (wid == 8) {
                if (phases & 1) {
                    const int h = (n >> 1) & 15;
                    int slot = 0; uint32_t par = 1;
#pragma unroll 1
                    for (int tile = 0; tile < 39; tile++) {
                        const CUtensorMap* map = tile >= 7 ? &mapX : (n < 32 ? &mapK : &mapV);
                        const int x0 = tile >= 7 ? 0 : h * DH, y = 64 * (tile >= 7 ? tile - 7 : tile) + 32 * (n & 1), ns = tile >= 7 ? 14 : 8;
#pragma unroll 1
                        for (int i = 0; i < ns; i++) {
                            mbar_wait(sb + G_BAR + (7 + slot) * 8, par);
                            if (elect_one()) {
                                mbar_expect(sb + G_BAR + slot * 8, 4096);
                                tma2d_pair(sb + G_RING + slot * 4096 + (n & 1) * 2048, map, x0 + 32 * i, y, sb + G_BAR + slot * 8);
                            }
                            if (++slot == NRING) { slot = 0; par ^= 1; }
                        }
                    }
                }
            } else if (wid == 9) {
                if (phases & 2) {
#pragma unroll 1
                    for (int k = 0; k < 8; k++) {
                        const int seg = k < 7 ? unit_segment(n, k, spare) : TAIL + (n >> 3);
                        if (k < 7 && seg >= TAIL) continue;
                        wait_count_warp(g_CNT + seg * 32, (epoch + 1) * 64, k < 7 ? 200 : 20);
                        fence_acq();
                        if (elect_one()) mbar_arrive(sb + G_RDY + k * 8);
                    }
                }
            } else if (phases & 1) {
#pragma unroll 1
                for (int q = wid - 10; q < 39; q += 2) {
                    mbar_wait(sb + G_PUB + q * 8, 0);
                    fence_rel();
                    if (elect_one()) {
                        st_relaxed(g_FT + n * 32 + (q & 1), epoch * 32 + (q >> 1) + 1);
                        if (q == 6) GT(1, 2);
                        if (q == 7) GT(1, 3);
                    }
                }
            }
        } else if (wid == 9 && spare && n < 68 && (phases & 2)) {
            int slot = 0; uint32_t par = 1;
#pragma unroll 1
            for (int i = n - 64; spare_segment(i) < TAIL; i += 4) {
                const int seg = spare_segment(i);
                wait_count_warp(g_CNT + seg * 32, (epoch + 1) * 64, 50);
                fence_acq();
                asm volatile("fence.proxy.async.global;" ::: "memory");
#pragma unroll 1
                for (int sh = (seg & (RS - 1)) * 16, h = 0; h < 16; h++, sh++) {
                    mbar_wait(sb + G_BAR + (7 + slot) * 8, par);
                    if (elect_one()) {
                        const uint32_t dst = sb + slot * PVS, bar = sb + G_BAR + slot * 8;
                        mbar_expect(bar, PVS);
                        bulk_g2s(dst, g_V + sh * 28672, 28672, bar); bulk_g2s(dst + PV_U, g_U + sh * 1792, 7168, bar); bulk_g2s(dst + PV_P, g_P + sh * 448, 1792, bar);
                    }
                    if (++slot == PV_N) { slot = 0; par ^= 1; }
                }
            }
        }
        cluster_wait();
    }
}

}

extern "C" void kernel_launch(void* const* d_in, const int* in_sizes, int n_in, void* d_out, int out_size) {
    typedef const __nv_bfloat16* bp;
    __nv_bfloat16* out = (__nv_bfloat16*)d_out;
    const SsmArgs ssm = {(bp)d_in[1], (bp)d_in[2], (bp)d_in[3], (bp)d_in[4], (bp)d_in[5], (bp)d_in[6]};
    const bp x = (bp)d_in[7], mem0 = (bp)d_in[8];
    static int nsm = 0;
    typedef CUresult (*EncodeFn)(CUtensorMap*, CUtensorMapDataType, cuuint32_t, void*, const cuuint64_t*, const cuuint64_t*, const cuuint32_t*,
                                 const cuuint32_t*, CUtensorMapInterleave, CUtensorMapSwizzle, CUtensorMapL2promotion, CUtensorMapFloatOOBfill);
    static EncodeFn encode = nullptr;
    if (!nsm) {
        cudaFuncSetAttribute(k_rec, cudaFuncAttributeMaxDynamicSharedMemorySize, R_SMEM);
        cudaFuncSetAttribute(k_bulk, cudaFuncAttributeMaxDynamicSharedMemorySize, G_SMEM);
        int dev = 0; cudaGetDevice(&dev);
        cudaDeviceGetAttribute(&nsm, cudaDevAttrMultiProcessorCount, dev);
        cudaDriverEntryPointQueryResult qr;
        cudaGetDriverEntryPoint("cuTensorMapEncodeTiled", (void**)&encode, cudaEnableDefault, &qr);
    }
    auto make_map = [&](const void* p, int rank, cuuint64_t d0, cuuint64_t d1, cuuint64_t d2, cuuint64_t s1, cuuint64_t s2,
                        cuuint32_t b0, cuuint32_t b1, cuuint32_t b2, CUtensorMapSwizzle sw) {
        CUtensorMap m;
        const cuuint64_t dims[3] = {d0, d1, d2}, strides[2] = {s1, s2};
        const cuuint32_t box[3] = {b0, b1, b2}, es[3] = {1, 1, 1};
        encode(&m, CU_TENSOR_MAP_DATA_TYPE_BFLOAT16, rank, (void*)p, dims, strides, box, es, CU_TENSOR_MAP_INTERLEAVE_NONE,
               sw, CU_TENSOR_MAP_L2_PROMOTION_L2_128B, CU_TENSOR_MAP_FLOAT_OOB_FILL_NONE);
        return m;
    };
    const CUtensorMap mapX = make_map(x, 2, D, S, 1, D * 2, 0, 32, 32, 1, CU_TENSOR_MAP_SWIZZLE_64B);
    const CUtensorMap mapXs = make_map(x, 2, D, S, 1, D * 2, 0, 64, 32, 1, CU_TENSOR_MAP_SWIZZLE_128B);
    const CUtensorMap mapU = make_map(d_in[0], 2, D, S, 1, D * 2, 0, 8, 256, 1, CU_TENSOR_MAP_SWIZZLE_NONE);
    const CUtensorMap mapY = make_map(out, 2, OUTW, S, 1, OUTW * 2, 0, 8, 128, 1, CU_TENSOR_MAP_SWIZZLE_NONE);
    const CUtensorMap mapQ = make_map(d_in[9], 2, 4096, D, 1, 8192, 0, 64, 224, 1, CU_TENSOR_MAP_SWIZZLE_128B);
    const CUtensorMap mapK = make_map(d_in[10], 2, 4096, D, 1, 8192, 0, 32, 32, 1, CU_TENSOR_MAP_SWIZZLE_64B);
    const CUtensorMap mapV = make_map(d_in[11], 2, 4096, D, 1, 8192, 0, 32, 32, 1, CU_TENSOR_MAP_SWIZZLE_64B);
    const CUtensorMap mapO = make_map(d_in[12], 3, 32, 4096, 14, D * 2, 64, 32, 64, 7, CU_TENSOR_MAP_SWIZZLE_64B);
    const int nbulk = nsm >= 132 ? 68 : 64;
    k_rec<<<64, 384, R_SMEM, cudaStreamPerThread>>>(mapXs, mapU, mapY, ssm, (const uint8_t*)x, mem0, (const uint8_t*)d_in[10],
                                                    (const uint8_t*)d_in[11], (unsigned)(64 + nbulk), 0u);
    cudaLaunchAttribute pdl[1];
    pdl[0].id = cudaLaunchAttributeProgrammaticStreamSerialization;
    pdl[0].val.programmaticStreamSerializationAllowed = 1;
    cudaLaunchConfig_t cfg = {};
    cfg.stream = cudaStreamPerThread;
    cfg.attrs = pdl; cfg.numAttrs = 1;
    cfg.gridDim = dim3(nbulk); cfg.blockDim = dim3(384); cfg.dynamicSmemBytes = G_SMEM;
    cudaLaunchKernelEx(&cfg, k_bulk, mapX, mapK, mapV, mapQ, mapO, out, (unsigned)(64 + nbulk), 3);
}
```
